```python
import torch

def _softmax(x, axis=-1):
    return torch.softmax(x, dim=axis)
def _gelu(x):
    return torch.nn.functional.gelu(x, approximate="tanh")
def _silu(x):
    return torch.nn.functional.silu(x)
def _sigmoid(x):
    return torch.sigmoid(x)
def _layernorm(x, axis=-1, eps=1e-5):
    m = x.mean(dim=axis, keepdim=True)
    v = x.var(dim=axis, keepdim=True, unbiased=False)
    return (x - m) / torch.sqrt(v + eps)
def _scatter_add(tgt, idx, src, axis=0):
    return tgt.clone().index_add_(axis, idx, src)
def _segment_sum(src, seg, n):
    out = torch.zeros((n,) + src.shape[1:], dtype=src.dtype)
    return out.index_add_(0, seg, src)
def _pad(x, pw):
    flat = tuple(v for pair in reversed(pw) for v in pair)
    return torch.nn.functional.pad(x, flat)

kernel_name = 'sequential_preLN__compressed_kv_cla__glu_gated_reglu__prompt'

def setup_inputs():

    _w = (lambda a: (lambda t: t.to(torch.bfloat16) if t.is_floating_point() else t)(torch.as_tensor(a)))
    def _A_setup():
        B, H, Sq, Sk, D, M = 1, 32, 2048, 2048, 128, 512
        Dc = 4 * D
        return {
            "x": _w((lambda *s: torch.randn(*s, dtype=torch.bfloat16) * 0.05)(B, Sq, M)),
            "c_kv": _w((lambda *s: torch.randn(*s, dtype=torch.bfloat16) * 0.4)(B, Sk, Dc)),
            "w_q": _w((lambda *s: torch.randn(*s, dtype=torch.bfloat16) * 1.6)(M, H, D) * (M ** -0.5)),
            "w_uk": _w((lambda *s: torch.randn(*s, dtype=torch.bfloat16) * 1.6)(Dc, H, D) * (Dc ** -0.5)),
            "w_uv": _w((lambda *s: torch.randn(*s, dtype=torch.bfloat16) * 0.4)(Dc, H, D) * (Dc ** -0.5)),
            "w_o": _w((lambda *s: torch.randn(*s, dtype=torch.bfloat16) * 0.4)(H, D, M) * ((H * D) ** -0.5)),
        }
    _A_in = _A_setup()

    def _B_setup():
        B, S, D, F = 1, 2048, 512, 1376
        return {
            "x": _w((lambda *s: torch.randn(*s, dtype=torch.bfloat16) * 0.05)(B, S, D)),
            "W_gate": _w((lambda *s: torch.randn(*s, dtype=torch.bfloat16) * 0.2)(D, F) * (2.0 / D) ** 0.5),
            "W_up": _w((lambda *s: torch.randn(*s, dtype=torch.bfloat16) * 0.2)(D, F) * (2.0 / D) ** 0.5),
            "W_down": _w((lambda *s: torch.randn(*s, dtype=torch.bfloat16) * 0.2)(F, D) * (1.0 / F) ** 0.5),
        }
    _B_in = _B_setup()

    return {
        "A_x": _A_in["x"],
        "A_c_kv": _A_in["c_kv"],
        "A_w_q": _A_in["w_q"],
        "A_w_uk": _A_in["w_uk"],
        "A_w_uv": _A_in["w_uv"],
        "A_w_o": _A_in["w_o"],
        "B_x": _B_in["x"],
        "B_W_gate": _B_in["W_gate"],
        "B_W_up": _B_in["W_up"],
        "B_W_down": _B_in["W_down"],
    }

def reference(A_x, A_c_kv, A_w_q, A_w_uk, A_w_uv, A_w_o, B_x, B_W_gate, B_W_up, B_W_down):
    def _A_ref(x, c_kv, w_q, w_uk, w_uv, w_o):
        B, Sq, M = x.shape[0], x.shape[1], x.shape[2]
        Sk = c_kv.shape[1]
        H, D = w_q.shape[1], w_q.shape[2]
        q = torch.einsum("bqm,mhd->bhqd", x, w_q)
        k = torch.einsum("bkc,chd->bhkd", c_kv, w_uk)
        v = torch.einsum("bkc,chd->bhkd", c_kv, w_uv)
        scores = torch.einsum("bhqd,bhkd->bhqk", q, k) * (D ** -0.5)
        off = Sk - Sq
        qi = torch.arange(Sq)[:, None]
        kj = torch.arange(Sk)[None, :]
        cmask = kj <= (qi + off)
        scores = torch.where(cmask[None, None], scores, -1e9)
        p = _softmax(scores, axis=-1)
        ctx = torch.einsum("bhqk,bhkd->bhqd", p, v)
        return torch.einsum("bhqd,hdm->bqm", ctx, w_o)

    def _B_ref(x, W_gate, W_up, W_down):
        gate = torch.einsum("bsd,df->bsf", x, W_gate)
        up = torch.einsum("bsd,df->bsf", x, W_up)
        gate = gate * (lambda x, dt: x.to(dt))(gate > 0, gate.dtype)
        h = gate * up
        return torch.einsum("bsf,fd->bsd", h, W_down)

    x = A_x
    h = x + _A_ref(_layernorm(x, axis=-1), A_c_kv, A_w_q, A_w_uk, A_w_uv, A_w_o)
    h2 = h + _B_ref(_layernorm(h, axis=-1), B_W_gate, B_W_up, B_W_down)
    return h2
```

```cpp
#include <cuda_runtime.h>
#include <cuda_bf16.h>
#include <cuda.h>
#include <stdint.h>

namespace {

constexpr int SEQ = 2048, DM = 512, NH = 32, HD = 128, FF = 1376;
typedef __nv_bfloat16 bf16;

__device__ __align__(1024) bf16 g_xn[SEQ * DM];
__device__ __align__(1024) bf16 g_q[NH * SEQ * HD];
__device__ __align__(1024) bf16 g_k[NH * SEQ * HD];
__device__ __align__(1024) bf16 g_v[NH * SEQ * HD];
__device__ __align__(1024) bf16 g_ctx[NH * SEQ * HD];
__device__ __align__(1024) bf16 g_h[SEQ * DM];
__device__ __align__(1024) bf16 g_act[SEQ * 1408];
__device__ __align__(1024) float2 g_stats[SEQ * 8];
__device__ __align__(1024) float g_cs[2 * 1408];

__device__ unsigned int g_team[32];
__device__ unsigned int g_ln_count[16];

__device__ __forceinline__ uint32_t smem_u32(const void* p) { return (uint32_t)__cvta_generic_to_shared(p); }
__device__ __forceinline__ void mbar_init(uint32_t bar, uint32_t cnt) {
  asm volatile("mbarrier.init.shared::cta.b64 [%0], %1;" ::"r"(bar), "r"(cnt));
}
__device__ __forceinline__ void mbar_expect_tx(uint32_t bar, uint32_t bytes) {
  asm volatile("mbarrier.arrive.expect_tx.shared::cta.b64 _, [%0], %1;" ::"r"(bar), "r"(bytes) : "memory");
}
__device__ __forceinline__ void mbar_arrive(uint32_t bar) {
  asm volatile("mbarrier.arrive.shared::cta.b64 _, [%0];" ::"r"(bar) : "memory");
}
__device__ __forceinline__ void mbar_wait(uint32_t bar, uint32_t parity) {
  asm volatile(
      "{\n.reg .pred p;\n.reg .u32 c;\n"
      "mov.u32 c, 0;\n"
      "WAIT_LOOP:\n"
      "mbarrier.try_wait.parity.shared::cta.b64 p, [%0], %1;\n"
      "@p bra WAIT_DONE;\n"
      "add.u32 c, c, 1;\n"
      "setp.lt.u32 p, c, 0x400000;\n"
      "@p bra WAIT_LOOP;\n"
      "trap;\n"
      "WAIT_DONE:\n}"
      ::"r"(bar), "r"(parity) : "memory");
}
__device__ __forceinline__ void spin_until(const unsigned int* ctr, unsigned int target) {
  asm volatile(
      "{\n.reg .pred p;\n.reg .u32 c, v;\n"
      "mov.u32 c, 0;\n"
      "SPIN_LOOP:\n"
      "ld.acquire.gpu.global.u32 v, [%0];\n"
      "setp.ge.u32 p, v, %1;\n"
      "@p bra SPIN_DONE;\n"
      "add.u32 c, c, 1;\n"
      "setp.lt.u32 p, c, 0x1000000;\n"
      "@p bra SPIN_LOOP;\n"
      "trap;\n"
      "SPIN_DONE:\n}"
      ::"l"(ctr), "r"(target) : "memory");
}
__device__ __forceinline__ void tma_load_2d(uint32_t dst, const CUtensorMap* map, int c0, int c1, uint32_t bar) {
  asm volatile("cp.async.bulk.tensor.2d.shared::cluster.global.mbarrier::complete_tx::bytes [%0], [%1, {%3, %4}], [%2];"
               ::"r"(dst), "l"(map), "r"(bar), "r"(c0), "r"(c1) : "memory");
}
__device__ __forceinline__ void tma_load_3d(uint32_t dst, const CUtensorMap* map, int c0, int c1, int c2, uint32_t bar) {
  asm volatile("cp.async.bulk.tensor.3d.shared::cluster.global.mbarrier::complete_tx::bytes [%0], [%1, {%3, %4, %5}], [%2];"
               ::"r"(dst), "l"(map), "r"(bar), "r"(c0), "r"(c1), "r"(c2) : "memory");
}
__device__ __forceinline__ void tma_store_2d(const CUtensorMap* map, uint32_t src, int c0, int c1) {
  asm volatile("cp.async.bulk.tensor.2d.global.shared::cta.bulk_group [%0, {%2, %3}], [%1];"
               ::"l"(map), "r"(src), "r"(c0), "r"(c1) : "memory");
}
__device__ __forceinline__ void tma_prefetch_desc(const CUtensorMap* map) {
  asm volatile("prefetch.tensormap [%0];" ::"l"(map) : "memory");
}
__device__ __forceinline__ void bulk_commit() { asm volatile("cp.async.bulk.commit_group;" ::: "memory"); }
template <int N> __device__ __forceinline__ void bulk_wait_read() { asm volatile("cp.async.bulk.wait_group.read %0;" ::"n"(N) : "memory"); }
template <int N> __device__ __forceinline__ void bulk_wait() { asm volatile("cp.async.bulk.wait_group %0;" ::"n"(N) : "memory"); }
__device__ __forceinline__ void fence_async_smem() { asm volatile("fence.proxy.async.shared::cta;" ::: "memory"); }
__device__ __forceinline__ void bar_sync(int id, int n) { asm volatile("bar.sync %0, %1;" ::"r"(id), "r"(n) : "memory"); }
__device__ __forceinline__ void bar_arrive(int id, int n) { asm volatile("bar.arrive %0, %1;" ::"r"(id), "r"(n) : "memory"); }
__device__ __forceinline__ void pdl_wait() { asm volatile("griddepcontrol.wait;" ::: "memory"); }
__device__ __forceinline__ void pdl_launch() { asm volatile("griddepcontrol.launch_dependents;" ::: "memory"); }
template <int N> __device__ __forceinline__ void reg_inc() { asm volatile("setmaxnreg.inc.sync.aligned.u32 %0;" ::"n"(N)); }
template <int N> __device__ __forceinline__ void reg_dec() { asm volatile("setmaxnreg.dec.sync.aligned.u32 %0;" ::"n"(N)); }
__device__ __forceinline__ void wgmma_fence() { asm volatile("wgmma.fence.sync.aligned;" ::: "memory"); }
__device__ __forceinline__ void wgmma_commit() { asm volatile("wgmma.commit_group.sync.aligned;" ::: "memory"); }
template <int N> __device__ __forceinline__ void wgmma_wait() { asm volatile("wgmma.wait_group.sync.aligned %0;" ::"n"(N) : "memory"); }
template <int N> __device__ __forceinline__ void fence_regs(float (&r)[N]) {
#pragma unroll
  for (int i = 0; i < N; i++) asm volatile("" : "+f"(r[i])::"memory");
}
template <int N> __device__ __forceinline__ void fence_regs(uint32_t (&r)[N]) {
#pragma unroll
  for (int i = 0; i < N; i++) asm volatile("" : "+r"(r[i])::"memory");
}
__device__ __forceinline__ uint32_t make_desc(uint32_t addr, uint32_t lbo_bytes) { return ((addr & 0x3FFFF) >> 4) | ((lbo_bytes >> 4) << 16); }
__device__ __forceinline__ uint32_t desc_add(uint32_t d, uint32_t bytes) { return d + (bytes >> 4); }
__device__ __forceinline__ uint32_t pack_bf16(float lo, float hi) {
  uint32_t r;
  asm("cvt.rn.bf16x2.f32 %0, %1, %2;" : "=r"(r) : "f"(hi), "f"(lo));
  return r;
}
__device__ __forceinline__ float bf_lo(uint32_t v) { return __uint_as_float(v << 16); }
__device__ __forceinline__ float bf_hi(uint32_t v) { return __uint_as_float(v & 0xffff0000u); }
__device__ __forceinline__ float ex2(float x) {
  float y;
  asm("ex2.approx.ftz.f32 %0, %1;" : "=f"(y) : "f"(x));
  return y;
}
__device__ __forceinline__ void stmatrix_x4(uint32_t addr, uint32_t a, uint32_t b, uint32_t c, uint32_t d) {
  asm volatile("stmatrix.sync.aligned.m8n8.x4.shared.b16 [%0], {%1, %2, %3, %4};"
               ::"r"(addr), "r"(a), "r"(b), "r"(c), "r"(d) : "memory");
}
__device__ __forceinline__ uint32_t align1024(uint32_t a) { return (a + 1023u) & ~1023u; }

#define WATCHDOG_DECL
#define WATCHDOG_RUN(n)
#define WATCHDOG_DONE()

#define PROF(kern, idx)

#define TRACE_DECL(role)
#define TRACE(tag)
#define TRACE_END()

#define QTRACE_DECL(role)
#define QTRACE(tag)
#define QTRACE_END()

#define XTRACE_DECL(role, kern)
#define XTRACE_PARAMS
#define XTRACE_ARGS
#define XTRACE(tag)
#define XTRACE_END()
template <int TB>
__device__ __forceinline__ void wgmma_ss_n128(float (&d)[64], uint32_t da, uint32_t db, int scale_d) {
  asm volatile("{\n.reg .pred p;\n.reg .b64 da, db;\nsetp.ne.b32 p, %66, 0;\nmov.b64 da, {%64, 0x40000040};\nmov.b64 db, {%65, 0x40000040};\n"
    "wgmma.mma_async.sync.aligned.m64n128k16.f32.bf16.bf16 "
    "{%0, %1, %2, %3, %4, %5, %6, %7, %8, %9, %10, %11, %12, %13, %14, %15, "
    "%16, %17, %18, %19, %20, %21, %22, %23, %24, %25, %26, %27, %28, %29, %30, %31, "
    "%32, %33, %34, %35, %36, %37, %38, %39, %40, %41, %42, %43, %44, %45, %46, %47, "
    "%48, %49, %50, %51, %52, %53, %54, %55, %56, %57, %58, %59, %60, %61, %62, %63}, "
    "da, db, p, 1, 1, 0, %67;\n}\n"
    :
      "+f"(d[0]), "+f"(d[1]), "+f"(d[2]), "+f"(d[3]), "+f"(d[4]), "+f"(d[5]), "+f"(d[6]), "+f"(d[7]),
      "+f"(d[8]), "+f"(d[9]), "+f"(d[10]), "+f"(d[11]), "+f"(d[12]), "+f"(d[13]), "+f"(d[14]), "+f"(d[15]),
      "+f"(d[16]), "+f"(d[17]), "+f"(d[18]), "+f"(d[19]), "+f"(d[20]), "+f"(d[21]), "+f"(d[22]), "+f"(d[23]),
      "+f"(d[24]), "+f"(d[25]), "+f"(d[26]), "+f"(d[27]), "+f"(d[28]), "+f"(d[29]), "+f"(d[30]), "+f"(d[31]),
      "+f"(d[32]), "+f"(d[33]), "+f"(d[34]), "+f"(d[35]), "+f"(d[36]), "+f"(d[37]), "+f"(d[38]), "+f"(d[39]),
      "+f"(d[40]), "+f"(d[41]), "+f"(d[42]), "+f"(d[43]), "+f"(d[44]), "+f"(d[45]), "+f"(d[46]), "+f"(d[47]),
      "+f"(d[48]), "+f"(d[49]), "+f"(d[50]), "+f"(d[51]), "+f"(d[52]), "+f"(d[53]), "+f"(d[54]), "+f"(d[55]),
      "+f"(d[56]), "+f"(d[57]), "+f"(d[58]), "+f"(d[59]), "+f"(d[60]), "+f"(d[61]), "+f"(d[62]), "+f"(d[63])
    : "r"(da), "r"(db), "r"(scale_d), "n"(TB));
}
template <int TB>
__device__ __forceinline__ void wgmma_rs_n128(float (&d)[64], uint32_t a0, uint32_t a1, uint32_t a2, uint32_t a3, uint32_t db, int scale_d) {
  asm volatile("{\n.reg .pred p;\n.reg .b64 db;\nsetp.ne.b32 p, %69, 0;\nmov.b64 db, {%68, 0x40000040};\n"
    "wgmma.mma_async.sync.aligned.m64n128k16.f32.bf16.bf16 "
    "{%0, %1, %2, %3, %4, %5, %6, %7, %8, %9, %10, %11, %12, %13, %14, %15, "
    "%16, %17, %18, %19, %20, %21, %22, %23, %24, %25, %26, %27, %28, %29, %30, %31, "
    "%32, %33, %34, %35, %36, %37, %38, %39, %40, %41, %42, %43, %44, %45, %46, %47, "
    "%48, %49, %50, %51, %52, %53, %54, %55, %56, %57, %58, %59, %60, %61, %62, %63}, "
    "{%64, %65, %66, %67}, db, p, 1, 1, %70;\n}\n"
    :
      "+f"(d[0]), "+f"(d[1]), "+f"(d[2]), "+f"(d[3]), "+f"(d[4]), "+f"(d[5]), "+f"(d[6]), "+f"(d[7]),
      "+f"(d[8]), "+f"(d[9]), "+f"(d[10]), "+f"(d[11]), "+f"(d[12]), "+f"(d[13]), "+f"(d[14]), "+f"(d[15]),
      "+f"(d[16]), "+f"(d[17]), "+f"(d[18]), "+f"(d[19]), "+f"(d[20]), "+f"(d[21]), "+f"(d[22]), "+f"(d[23]),
      "+f"(d[24]), "+f"(d[25]), "+f"(d[26]), "+f"(d[27]), "+f"(d[28]), "+f"(d[29]), "+f"(d[30]), "+f"(d[31]),
      "+f"(d[32]), "+f"(d[33]), "+f"(d[34]), "+f"(d[35]), "+f"(d[36]), "+f"(d[37]), "+f"(d[38]), "+f"(d[39]),
      "+f"(d[40]), "+f"(d[41]), "+f"(d[42]), "+f"(d[43]), "+f"(d[44]), "+f"(d[45]), "+f"(d[46]), "+f"(d[47]),
      "+f"(d[48]), "+f"(d[49]), "+f"(d[50]), "+f"(d[51]), "+f"(d[52]), "+f"(d[53]), "+f"(d[54]), "+f"(d[55]),
      "+f"(d[56]), "+f"(d[57]), "+f"(d[58]), "+f"(d[59]), "+f"(d[60]), "+f"(d[61]), "+f"(d[62]), "+f"(d[63])
    : "r"(a0), "r"(a1), "r"(a2), "r"(a3), "r"(db), "r"(scale_d), "n"(TB));
}
template <int TB>
__device__ __forceinline__ void wgmma_ss_n176(float (&d)[88], uint32_t da, uint32_t db, int scale_d) {
  asm volatile("{\n.reg .pred p;\n.reg .b64 da, db;\nsetp.ne.b32 p, %90, 0;\nmov.b64 da, {%88, 0x40000040};\nmov.b64 db, {%89, 0x40000040};\n"
    "wgmma.mma_async.sync.aligned.m64n176k16.f32.bf16.bf16 "
    "{%0, %1, %2, %3, %4, %5, %6, %7, %8, %9, %10, %11, %12, %13, %14, %15, "
    "%16, %17, %18, %19, %20, %21, %22, %23, %24, %25, %26, %27, %28, %29, %30, %31, "
    "%32, %33, %34, %35, %36, %37, %38, %39, %40, %41, %42, %43, %44, %45, %46, %47, "
    "%48, %49, %50, %51, %52, %53, %54, %55, %56, %57, %58, %59, %60, %61, %62, %63, "
    "%64, %65, %66, %67, %68, %69, %70, %71, %72, %73, %74, %75, %76, %77, %78, %79, "
    "%80, %81, %82, %83, %84, %85, %86, %87}, "
    "da, db, p, 1, 1, 0, %91;\n}\n"
    :
      "+f"(d[0]), "+f"(d[1]), "+f"(d[2]), "+f"(d[3]), "+f"(d[4]), "+f"(d[5]), "+f"(d[6]), "+f"(d[7]),
      "+f"(d[8]), "+f"(d[9]), "+f"(d[10]), "+f"(d[11]), "+f"(d[12]), "+f"(d[13]), "+f"(d[14]), "+f"(d[15]),
      "+f"(d[16]), "+f"(d[17]), "+f"(d[18]), "+f"(d[19]), "+f"(d[20]), "+f"(d[21]), "+f"(d[22]), "+f"(d[23]),
      "+f"(d[24]), "+f"(d[25]), "+f"(d[26]), "+f"(d[27]), "+f"(d[28]), "+f"(d[29]), "+f"(d[30]), "+f"(d[31]),
      "+f"(d[32]), "+f"(d[33]), "+f"(d[34]), "+f"(d[35]), "+f"(d[36]), "+f"(d[37]), "+f"(d[38]), "+f"(d[39]),
      "+f"(d[40]), "+f"(d[41]), "+f"(d[42]), "+f"(d[43]), "+f"(d[44]), "+f"(d[45]), "+f"(d[46]), "+f"(d[47]),
      "+f"(d[48]), "+f"(d[49]), "+f"(d[50]), "+f"(d[51]), "+f"(d[52]), "+f"(d[53]), "+f"(d[54]), "+f"(d[55]),
      "+f"(d[56]), "+f"(d[57]), "+f"(d[58]), "+f"(d[59]), "+f"(d[60]), "+f"(d[61]), "+f"(d[62]), "+f"(d[63]),
      "+f"(d[64]), "+f"(d[65]), "+f"(d[66]), "+f"(d[67]), "+f"(d[68]), "+f"(d[69]), "+f"(d[70]), "+f"(d[71]),
      "+f"(d[72]), "+f"(d[73]), "+f"(d[74]), "+f"(d[75]), "+f"(d[76]), "+f"(d[77]), "+f"(d[78]), "+f"(d[79]),
      "+f"(d[80]), "+f"(d[81]), "+f"(d[82]), "+f"(d[83]), "+f"(d[84]), "+f"(d[85]), "+f"(d[86]), "+f"(d[87])
    : "r"(da), "r"(db), "r"(scale_d), "n"(TB));
}
template <int TB>
__device__ __forceinline__ void wgmma_ss_n256(float (&d)[128], uint32_t da, uint32_t db, int scale_d) {
  asm volatile("{\n.reg .pred p;\n.reg .b64 da, db;\nsetp.ne.b32 p, %130, 0;\nmov.b64 da, {%128, 0x40000040};\nmov.b64 db, {%129, 0x40000040};\n"
    "wgmma.mma_async.sync.aligned.m64n256k16.f32.bf16.bf16 "
    "{%0, %1, %2, %3, %4, %5, %6, %7, %8, %9, %10, %11, %12, %13, %14, %15, "
    "%16, %17, %18, %19, %20, %21, %22, %23, %24, %25, %26, %27, %28, %29, %30, %31, "
    "%32, %33, %34, %35, %36, %37, %38, %39, %40, %41, %42, %43, %44, %45, %46, %47, "
    "%48, %49, %50, %51, %52, %53, %54, %55, %56, %57, %58, %59, %60, %61, %62, %63, "
    "%64, %65, %66, %67, %68, %69, %70, %71, %72, %73, %74, %75, %76, %77, %78, %79, "
    "%80, %81, %82, %83, %84, %85, %86, %87, %88, %89, %90, %91, %92, %93, %94, %95, "
    "%96, %97, %98, %99, %100, %101, %102, %103, %104, %105, %106, %107, %108, %109, %110, %111, "
    "%112, %113, %114, %115, %116, %117, %118, %119, %120, %121, %122, %123, %124, %125, %126, %127}, "
    "da, db, p, 1, 1, 0, %131;\n}\n"
    :
      "+f"(d[0]), "+f"(d[1]), "+f"(d[2]), "+f"(d[3]), "+f"(d[4]), "+f"(d[5]), "+f"(d[6]), "+f"(d[7]),
      "+f"(d[8]), "+f"(d[9]), "+f"(d[10]), "+f"(d[11]), "+f"(d[12]), "+f"(d[13]), "+f"(d[14]), "+f"(d[15]),
      "+f"(d[16]), "+f"(d[17]), "+f"(d[18]), "+f"(d[19]), "+f"(d[20]), "+f"(d[21]), "+f"(d[22]), "+f"(d[23]),
      "+f"(d[24]), "+f"(d[25]), "+f"(d[26]), "+f"(d[27]), "+f"(d[28]), "+f"(d[29]), "+f"(d[30]), "+f"(d[31]),
      "+f"(d[32]), "+f"(d[33]), "+f"(d[34]), "+f"(d[35]), "+f"(d[36]), "+f"(d[37]), "+f"(d[38]), "+f"(d[39]),
      "+f"(d[40]), "+f"(d[41]), "+f"(d[42]), "+f"(d[43]), "+f"(d[44]), "+f"(d[45]), "+f"(d[46]), "+f"(d[47]),
      "+f"(d[48]), "+f"(d[49]), "+f"(d[50]), "+f"(d[51]), "+f"(d[52]), "+f"(d[53]), "+f"(d[54]), "+f"(d[55]),
      "+f"(d[56]), "+f"(d[57]), "+f"(d[58]), "+f"(d[59]), "+f"(d[60]), "+f"(d[61]), "+f"(d[62]), "+f"(d[63]),
      "+f"(d[64]), "+f"(d[65]), "+f"(d[66]), "+f"(d[67]), "+f"(d[68]), "+f"(d[69]), "+f"(d[70]), "+f"(d[71]),
      "+f"(d[72]), "+f"(d[73]), "+f"(d[74]), "+f"(d[75]), "+f"(d[76]), "+f"(d[77]), "+f"(d[78]), "+f"(d[79]),
      "+f"(d[80]), "+f"(d[81]), "+f"(d[82]), "+f"(d[83]), "+f"(d[84]), "+f"(d[85]), "+f"(d[86]), "+f"(d[87]),
      "+f"(d[88]), "+f"(d[89]), "+f"(d[90]), "+f"(d[91]), "+f"(d[92]), "+f"(d[93]), "+f"(d[94]), "+f"(d[95]),
      "+f"(d[96]), "+f"(d[97]), "+f"(d[98]), "+f"(d[99]), "+f"(d[100]), "+f"(d[101]), "+f"(d[102]), "+f"(d[103]),
      "+f"(d[104]), "+f"(d[105]), "+f"(d[106]), "+f"(d[107]), "+f"(d[108]), "+f"(d[109]), "+f"(d[110]), "+f"(d[111]),
      "+f"(d[112]), "+f"(d[113]), "+f"(d[114]), "+f"(d[115]), "+f"(d[116]), "+f"(d[117]), "+f"(d[118]), "+f"(d[119]),
      "+f"(d[120]), "+f"(d[121]), "+f"(d[122]), "+f"(d[123]), "+f"(d[124]), "+f"(d[125]), "+f"(d[126]), "+f"(d[127])
    : "r"(da), "r"(db), "r"(scale_d), "n"(TB));
}
constexpr int KV_STAGES = 4;
constexpr int KV_STAGE_BYTES = 16384 + 32768;
constexpr int KV_SMEM = KV_STAGES * KV_STAGE_BYTES + 1024 + 256;

__device__ __forceinline__ void st_global_v4(void* p, uint32_t a, uint32_t b, uint32_t c, uint32_t d) {
  asm volatile("st.global.v4.b32 [%0], {%1, %2, %3, %4};" ::"l"(p), "r"(a), "r"(b), "r"(c), "r"(d) : "memory");
}

__global__ void __launch_bounds__(384, 1)
qkv_kernel(const __grid_constant__ CUtensorMap mCkv, const __grid_constant__ CUtensorMap mXn, const __grid_constant__ CUtensorMap mWk,
           const __grid_constant__ CUtensorMap mWv, const __grid_constant__ CUtensorMap mWq, const bf16* __restrict__ x,
           const bf16* __restrict__ w_gate, const bf16* __restrict__ w_up) {
  extern __shared__ uint8_t smem_raw[];
  const uint32_t base = align1024(smem_u32(smem_raw));
  const uint32_t bars = base + KV_STAGES * KV_STAGE_BYTES;
  WATCHDOG_DECL
  if (threadIdx.x == 0) {
    for (int i = 0; i < KV_STAGES; i++) {
      mbar_init(bars + i * 8, 1);
      mbar_init(bars + 64 + i * 8, 2);
    }
    asm volatile("fence.mbarrier_init.release.cluster;" ::: "memory");
  }
  if (threadIdx.x == 0) { PROF(0, 0) }
  if (blockIdx.x == 0 && threadIdx.x < 32) g_team[threadIdx.x] = 0;
  __syncthreads();
  pdl_launch();
  const int mblk = blockIdx.x & 15, ngrp = blockIdx.x >> 4;
  const int wg = threadIdx.x >> 7, warp = (threadIdx.x >> 5) & 3, lane = threadIdx.x & 31;
  if (wg == 0) {
    reg_dec<56>();
    if (warp == 0) {
      if (lane == 0) {
        const CUtensorMap* mW = ngrp < 4 ? &mWk : &mWv;
        for (int it = 0; it < 48; it++) {
          const int t = it >> 3, k = it & 7, st = it & 3;
          if (it == 32) {
            spin_until(g_ln_count + mblk, 24);
            asm volatile("fence.proxy.async.global;" ::: "memory");
          }
          mbar_wait(bars + 64 + st * 8, ((it >> 2) & 1) ^ 1);
          const uint32_t sa = base + st * KV_STAGE_BYTES;
          mbar_expect_tx(bars + st * 8, KV_STAGE_BYTES);
          if (t < 4) {
            tma_load_2d(sa, &mCkv, k * 64, mblk * 128, bars + st * 8);
            tma_load_3d(sa + 16384, mW, 0, k * 64, ((ngrp & 3) * 4 + t) * 4, bars + st * 8);
          } else {
            tma_load_2d(sa, &mXn, k * 64, mblk * 128, bars + st * 8);
            tma_load_3d(sa + 16384, &mWq, 0, k * 64, (ngrp * 2 + t - 4) * 4, bars + st * 8);
          }
        }
      }
    } else {
      for (int r = warp - 1; r < 16; r += 3) {
        const int row = blockIdx.x * 16 + r;
        const uint4* src = reinterpret_cast<const uint4*>(x + (size_t)row * DM);
        uint4 v0 = __ldg(src + lane), v1 = __ldg(src + 32 + lane);
        float f[16];
        const uint32_t u[8] = {v0.x, v0.y, v0.z, v0.w, v1.x, v1.y, v1.z, v1.w};
        float s = 0.f;
#pragma unroll
        for (int i = 0; i < 8; i++) { f[2 * i] = bf_lo(u[i]); f[2 * i + 1] = bf_hi(u[i]); s += f[2 * i] + f[2 * i + 1]; }
#pragma unroll
        for (int o = 16; o > 0; o >>= 1) s += __shfl_xor_sync(0xffffffffu, s, o);
        const float mean = s * (1.f / DM);
        float q = 0.f;
#pragma unroll
        for (int i = 0; i < 16; i++) { f[i] -= mean; q += f[i] * f[i]; }
#pragma unroll
        for (int o = 16; o > 0; o >>= 1) q += __shfl_xor_sync(0xffffffffu, q, o);
        const float rstd = 1.f / sqrtf(q * (1.f / DM) + 1e-5f);
        uint4 o0, o1;
        o0.x = pack_bf16(f[0] * rstd, f[1] * rstd);   o0.y = pack_bf16(f[2] * rstd, f[3] * rstd);
        o0.z = pack_bf16(f[4] * rstd, f[5] * rstd);   o0.w = pack_bf16(f[6] * rstd, f[7] * rstd);
        o1.x = pack_bf16(f[8] * rstd, f[9] * rstd);   o1.y = pack_bf16(f[10] * rstd, f[11] * rstd);
        o1.z = pack_bf16(f[12] * rstd, f[13] * rstd); o1.w = pack_bf16(f[14] * rstd, f[15] * rstd);
        uint4* dst = reinterpret_cast<uint4*>(g_xn + (size_t)row * DM);
        dst[lane] = o0;
        dst[32 + lane] = o1;
      }
      __threadfence();
      __syncwarp();
      if (lane == 0) atomicAdd(g_ln_count + (blockIdx.x >> 3), 1u);
      const int task = blockIdx.x * 3 + (warp - 1);
      if (task < 352) {
        const int mat = task / 176, grp = task % 176;
        float a[8];
#pragma unroll
        for (int i = 0; i < 8; i++) a[i] = 0.f;
        if (grp < FF / 8) {
          const bf16* w = (mat ? w_up : w_gate) + grp * 8;
#pragma unroll 4
          for (int r = lane; r < DM; r += 32) {
            const uint4 v = __ldg(reinterpret_cast<const uint4*>(w + (size_t)r * FF));
            a[0] += bf_lo(v.x); a[1] += bf_hi(v.x); a[2] += bf_lo(v.y); a[3] += bf_hi(v.y);
            a[4] += bf_lo(v.z); a[5] += bf_hi(v.z); a[6] += bf_lo(v.w); a[7] += bf_hi(v.w);
          }
#pragma unroll
          for (int i = 0; i < 8; i++)
#pragma unroll
            for (int o = 16; o > 0; o >>= 1) a[i] += __shfl_xor_sync(0xffffffffu, a[i], o);
        }
        if (lane == 0) {
          float4* dst = reinterpret_cast<float4*>(g_cs + mat * 1408 + grp * 8);
          dst[0] = make_float4(a[0], a[1], a[2], a[3]);
          dst[1] = make_float4(a[4], a[5], a[6], a[7]);
        }
      }
      WATCHDOG_RUN(2)
    }
  } else {
    reg_inc<224>();
    const int cw = wg - 1;
    const int tid = threadIdx.x & 127;
    if (cw == 1) bar_arrive(1, 256);
    QTRACE_DECL(1 + cw)
    float acc[128];
    uint32_t pk[64];

    const size_t thr_off = (size_t)(mblk * 128 + cw * 64 + warp * 16 + (lane >> 2)) * HD + (lane & 3) * 8;
    bf16* const kv_out = (ngrp < 4 ? g_k : g_v) + thr_off;
    bf16* prev_out = nullptr;
    auto store_piece = [&](int i) {
      bf16* dst = prev_out + (size_t)(i >> 2) * SEQ * HD + (i & 3) * 32;
      st_global_v4(dst, pk[8 * i], pk[8 * i + 2], pk[8 * i + 4], pk[8 * i + 6]);
      st_global_v4(dst + 8 * HD, pk[8 * i + 1], pk[8 * i + 3], pk[8 * i + 5], pk[8 * i + 7]);
    };
    for (int t = 0; t < 6; t++) {
      QTRACE(0x100 + t)
#pragma unroll
      for (int k = 0; k < 8; k++) {
        const int st = k & 3;
        if (k == 1 || k == 4 || k == 5) { QTRACE(30 + k) }
        mbar_wait(bars + st * 8, (k >> 2) & 1);
        const uint32_t sa = base + st * KV_STAGE_BYTES;
        const uint32_t da = make_desc(sa + cw * 8192, 16);
        const uint32_t db = make_desc(sa + 16384, 8192);
        bar_sync(1 + cw, 256);
        wgmma_fence();
#pragma unroll
        for (int kk = 0; kk < 4; kk++) wgmma_ss_n256<1>(acc, desc_add(da, kk * 32), desc_add(db, kk * 2048), (k | kk) != 0);
        wgmma_commit();
        bar_arrive(2 - cw, 256);
        if (t > 0) store_piece(k);
        if (k > 0) {
          wgmma_wait<1>();
          if (tid == 0) mbar_arrive(bars + 64 + ((k - 1) & 3) * 8);
        }
      }
      wgmma_wait<0>();
      if (tid == 0) mbar_arrive(bars + 64 + 3 * 8);
      fence_regs(acc);
      QTRACE(40)
#pragma unroll
      for (int i = 0; i < 64; i++) pk[i] = pack_bf16(acc[2 * i], acc[2 * i + 1]);
      prev_out = t < 4 ? kv_out + (size_t)(((ngrp & 3) * 4 + t) * 2) * SEQ * HD
                       : g_q + thr_off + (size_t)((ngrp * 2 + t - 4) * 2) * SEQ * HD;
    }
    QTRACE(41)
#pragma unroll
    for (int i = 0; i < 8; i++) store_piece(i);
    QTRACE(42)
    QTRACE_END()

    if (tid == 0) { PROF(0, 2 + cw) }
    WATCHDOG_DONE()
  }
}
constexpr int AT_SLOTS = 7;
constexpr int AT_SMEM = AT_SLOTS * 32768 + 1024 + 256;
struct AttnSched {
  int start[134];
  int tile[NH * 16];
};

struct RingPos {
  int slot;
  uint32_t phase;
  __device__ __forceinline__ void next() {
    if (++slot == AT_SLOTS) { slot = 0; phase ^= 1; }
  }
};

constexpr float SM_C = 0.08838834764831845f * 1.4426950408889634f;
constexpr float SM_LIMIT = 16384.f;

__device__ __forceinline__ void exp_pack(const float (&s)[64], uint32_t (&p)[32], float n0, float n1, float& r0, float& r1) {
  float a0 = 0.f, a1 = 0.f, b0 = 0.f, b1 = 0.f;
#pragma unroll
  for (int i = 0; i < 16; i++) {
    const float e0 = ex2(fmaf(s[4 * i], SM_C, n0)), e1 = ex2(fmaf(s[4 * i + 1], SM_C, n0));
    const float e2 = ex2(fmaf(s[4 * i + 2], SM_C, n1)), e3 = ex2(fmaf(s[4 * i + 3], SM_C, n1));
    a0 += e0;
    b0 += e1;
    a1 += e2;
    b1 += e3;
    p[2 * i] = pack_bf16(e0, e1);
    p[2 * i + 1] = pack_bf16(e2, e3);
  }
  r0 = a0 + b0;
  r1 = a1 + b1;
}

__device__ __forceinline__ void refresh_max(const float (&s)[64], float (&o)[64], float& m0, float& m1, float& l0, float& l1) {
  float a0 = fmaxf(s[0], s[1]), a1 = fmaxf(s[2], s[3]), b0 = fmaxf(s[4], s[5]), b1 = fmaxf(s[6], s[7]);
#pragma unroll
  for (int i = 2; i < 16; i += 2) {
    a0 = fmaxf(a0, fmaxf(s[4 * i], s[4 * i + 1]));
    a1 = fmaxf(a1, fmaxf(s[4 * i + 2], s[4 * i + 3]));
    b0 = fmaxf(b0, fmaxf(s[4 * i + 4], s[4 * i + 5]));
    b1 = fmaxf(b1, fmaxf(s[4 * i + 6], s[4 * i + 7]));
  }
  a0 = fmaxf(a0, b0);
  a1 = fmaxf(a1, b1);
  a0 = fmaxf(a0, __shfl_xor_sync(0xffffffffu, a0, 1));
  a1 = fmaxf(a1, __shfl_xor_sync(0xffffffffu, a1, 1));
  a0 = fmaxf(a0, __shfl_xor_sync(0xffffffffu, a0, 2));
  a1 = fmaxf(a1, __shfl_xor_sync(0xffffffffu, a1, 2));
  a0 = fmaxf(a0, m0);
  a1 = fmaxf(a1, m1);
  const float sc0 = ex2((m0 - a0) * SM_C), sc1 = ex2((m1 - a1) * SM_C);
  m0 = a0;
  m1 = a1;
  l0 *= sc0;
  l1 *= sc1;
#pragma unroll
  for (int i = 0; i < 16; i++) {
    o[4 * i] *= sc0;
    o[4 * i + 1] *= sc0;
    o[4 * i + 2] *= sc1;
    o[4 * i + 3] *= sc1;
  }
}

__device__ __forceinline__ void mask_diag(float (&s)[64], int cw, int warp, int lane, float& m0, float& m1) {
  const int t0 = cw * 64 + warp * 16 + (lane >> 2) - (lane & 3) * 2;
#pragma unroll
  for (int i = 0; i < 16; i++) {
    if (8 * i > t0) s[4 * i] = -INFINITY;
    if (8 * i + 1 > t0) s[4 * i + 1] = -INFINITY;
    if (8 * (i - 1) > t0) s[4 * i + 2] = -INFINITY;
    if (8 * (i - 1) + 1 > t0) s[4 * i + 3] = -INFINITY;
  }
  m0 = __shfl_sync(0xffffffffu, s[0], lane & 28);
  m1 = __shfl_sync(0xffffffffu, s[2], lane & 28);
}

__device__ __forceinline__ void load_q_frags(uint32_t (&q)[32], uint32_t sq, int cw, int warp, int lane) {
  const int row = cw * 64 + warp * 16 + (lane & 7) + ((lane >> 3) & 1) * 8;
  const uint32_t rbase = sq + row * 128;
#pragma unroll
  for (int j = 0; j < 8; j++) {
    const int chunk = (2 * j + (lane >> 4)) & 7;
    asm volatile("ldmatrix.sync.aligned.m8n8.x4.shared.b16 {%0, %1, %2, %3}, [%4];"
                 : "=r"(q[4 * j]), "=r"(q[4 * j + 1]), "=r"(q[4 * j + 2]), "=r"(q[4 * j + 3])
                 : "r"(rbase + (j >> 2) * 16384 + ((chunk ^ (row & 7)) << 4)) : "memory");
  }
}

__device__ __forceinline__ void write_ctx(const float (&o)[64], float l0, float l1, bf16* dst) {
  l0 += __shfl_xor_sync(0xffffffffu, l0, 1);
  l1 += __shfl_xor_sync(0xffffffffu, l1, 1);
  l0 += __shfl_xor_sync(0xffffffffu, l0, 2);
  l1 += __shfl_xor_sync(0xffffffffu, l1, 2);
  const float i0 = __frcp_rn(l0), i1 = __frcp_rn(l1);
#pragma unroll
  for (int a = 0; a < 4; a++) {
    st_global_v4(dst + 32 * a, pack_bf16(o[16 * a] * i0, o[16 * a + 1] * i0), pack_bf16(o[16 * a + 4] * i0, o[16 * a + 5] * i0),
                 pack_bf16(o[16 * a + 8] * i0, o[16 * a + 9] * i0), pack_bf16(o[16 * a + 12] * i0, o[16 * a + 13] * i0));
    st_global_v4(dst + 32 * a + 8 * HD, pack_bf16(o[16 * a + 2] * i1, o[16 * a + 3] * i1), pack_bf16(o[16 * a + 6] * i1, o[16 * a + 7] * i1),
                 pack_bf16(o[16 * a + 10] * i1, o[16 * a + 11] * i1), pack_bf16(o[16 * a + 14] * i1, o[16 * a + 15] * i1));
  }
}

__global__ void __launch_bounds__(384, 1)
attn_kernel(const __grid_constant__ CUtensorMap mQ, const __grid_constant__ CUtensorMap mK, const __grid_constant__ CUtensorMap mV,
            const __grid_constant__ AttnSched sched) {
  extern __shared__ uint8_t smem_raw[];
  const uint32_t base = align1024(smem_u32(smem_raw));
  const uint32_t bar_full = base + AT_SLOTS * 32768, bar_empty = bar_full + 64;
  WATCHDOG_DECL
  if (threadIdx.x == 0) {
    for (int i = 0; i < AT_SLOTS; i++) {
      mbar_init(bar_full + i * 8, 1);
      mbar_init(bar_empty + i * 8, 2);
    }
    asm volatile("fence.mbarrier_init.release.cluster;" ::: "memory");
  }
  if (threadIdx.x == 0) { PROF(1, 0) }
  __syncthreads();
  pdl_launch();
  const int wg = threadIdx.x >> 7, warp = (threadIdx.x >> 5) & 3, lane = threadIdx.x & 31;
  const int t_begin = sched.start[blockIdx.x], t_end = sched.start[blockIdx.x + 1];
  if (wg == 0) {
    reg_dec<24>();
    if (warp == 0 && lane == 0) {
      RingPos rp{0, 1};
      auto load = [&](const CUtensorMap* m, int row) {
        mbar_wait(bar_empty + rp.slot * 8, rp.phase);
        const uint32_t dst = base + rp.slot * 32768, fb = bar_full + rp.slot * 8;
        mbar_expect_tx(fb, 32768);
        tma_load_2d(dst, m, 0, row, fb);
        tma_load_2d(dst + 16384, m, 64, row, fb);
        rp.next();
      };
      pdl_wait();
      PROF(1, 1)
      if (blockIdx.x == 0)
        for (int i = 0; i < 16; i++) g_ln_count[i] = 0;
      int prev_v = -1;
      for (int ti = t_begin; ti < t_end; ti++) {
        const int tile = sched.tile[ti], h = tile >> 4, qb = tile & 15;
        if (ti == t_begin) load(&mQ, h * SEQ + qb * 128);
        for (int j = qb; j >= 0; j--) {
          if (prev_v >= 0) load(&mV, prev_v);
          load(&mK, h * SEQ + j * 128);
          prev_v = h * SEQ + j * 128;
          if (j == 0 && ti + 1 < t_end) {
            const int nt = sched.tile[ti + 1];
            load(&mQ, (nt >> 4) * SEQ + (nt & 15) * 128);
          }
        }
      }
      if (prev_v >= 0) load(&mV, prev_v);
    }
    WATCHDOG_RUN(2)
  } else {
    reg_inc<240>();
    const int cw = wg - 1;
    const int tid = threadIdx.x & 127;
    RingPos rp{0, 0};
    auto take = [&](int& slot) {
      mbar_wait(bar_full + rp.slot * 8, rp.phase);
      slot = rp.slot;
      rp.next();
    };
    auto release = [&](int slot) {
      if (tid == 0) mbar_arrive(bar_empty + slot * 8);
    };
    TRACE_DECL(1 + cw)
    if (t_begin < t_end) {
      if (cw == 1) bar_arrive(1, 256);
      float s[64], o[64];
      uint32_t q[32], p[32];
      float m0, m1, l0 = 0.f, l1 = 0.f;
      auto ctx_ptr = [&](int t) {
        return g_ctx + (size_t)((t >> 4) * SEQ + (t & 15) * 128 + cw * 64 + warp * 16 + (lane >> 2)) * HD + (lane & 3) * 8;
      };
      int slot_q = 0, slot_v = 0, slot_k = 0;
      auto issue_pv = [&](bool accumulate) {
        const uint32_t dv = make_desc(base + slot_v * 32768, 16384);
#pragma unroll
        for (int kk = 0; kk < 8; kk++)
          wgmma_rs_n128<1>(o, p[4 * kk], p[4 * kk + 1], p[4 * kk + 2], p[4 * kk + 3], desc_add(dv, kk * 2048), kk != 0 || accumulate);
      };
      auto issue_qk = [&]() {
        const uint32_t dk = make_desc(base + slot_k * 32768, 16);
#pragma unroll
        for (int kk = 0; kk < 8; kk++)
          wgmma_rs_n128<0>(s, q[4 * kk], q[4 * kk + 1], q[4 * kk + 2], q[4 * kk + 3],
                           desc_add(dk, (kk >> 2) * 16384 + (kk & 3) * 32), kk != 0);
      };
      auto take_next = [&](bool last_block, bool more_tiles) {
        if (last_block && more_tiles) take(slot_q);
        take(slot_v);
        if (!last_block || more_tiles) take(slot_k);
      };

      int ti = t_begin;
      int j = sched.tile[ti] & 15;
      TRACE(0x100 + j)
      take(slot_q);
      load_q_frags(q, base + slot_q * 32768, cw, warp, lane);
      release(slot_q);
      take(slot_k);
      bar_sync(1 + cw, 256);
      wgmma_fence();
      issue_qk();
      wgmma_commit();
      bar_arrive(2 - cw, 256);
      int done_k = slot_k;
      bool more = ti + 1 < t_end;
      take_next(j == 0, more);
#pragma unroll
      for (int i = 0; i < 64; i++) o[i] = 0.f;
      wgmma_wait<0>();
      release(done_k);
      fence_regs(s);
      mask_diag(s, cw, warp, lane, m0, m1);
      bool fresh = true;
#pragma unroll 1
      while (true) {
        float r0, r1;
        exp_pack(s, p, -m0 * SM_C, -m1 * SM_C, r0, r1);
        if (__any_sync(0xffffffffu, !(r0 <= SM_LIMIT && r1 <= SM_LIMIT))) {
          refresh_max(s, o, m0, m1, l0, l1);
          exp_pack(s, p, -m0 * SM_C, -m1 * SM_C, r0, r1);
        }
        l0 += r0;
        l1 += r1;
        if (j == 0) {
          if (!more) break;
          load_q_frags(q, base + slot_q * 32768, cw, warp, lane);
          release(slot_q);
        }
        bar_sync(1 + cw, 256);
        wgmma_fence();
        issue_pv(!fresh);
        issue_qk();
        wgmma_commit();
        bar_arrive(2 - cw, 256);
        const int done_v = slot_v;
        done_k = slot_k;
        fresh = j == 0;
        if (fresh) {
          j = sched.tile[++ti] & 15;
          more = ti + 1 < t_end;
        } else {
          j--;
        }
        take_next(j == 0, more);
        wgmma_wait<0>();
        release(done_v);
        release(done_k);
        fence_regs(s);
        fence_regs(o);
        if (fresh) {
          write_ctx(o, l0, l1, ctx_ptr(sched.tile[ti - 1]));
          TRACE(22)
          TRACE(0x100 + j)
          mask_diag(s, cw, warp, lane, m0, m1);
          l0 = 0.f;
          l1 = 0.f;
        }
      }
      bar_sync(1 + cw, 256);
      wgmma_fence();
      issue_pv(!fresh);
      wgmma_commit();
      bar_arrive(2 - cw, 256);
      wgmma_wait<0>();
      fence_regs(o);
      write_ctx(o, l0, l1, ctx_ptr(sched.tile[t_end - 1]));
      TRACE(22)
    }
    TRACE_END()
    if (tid == 0) { PROF(1, 2 + cw) }
    WATCHDOG_DONE()
  }
}
constexpr int TL_XBUF = 196608;
constexpr int TL_CS = TL_XBUF + 32768;
constexpr int TL_BARS = TL_CS + 1408;
constexpr int TL_SMEM = TL_BARS + 192 + 1024;
constexpr int ACT_PITCH = 1408;

__device__ __forceinline__ void tma_load_5d(uint32_t dst, const CUtensorMap* map, int c0, int c4, uint32_t bar) {
  asm volatile("cp.async.bulk.tensor.5d.shared::cluster.global.mbarrier::complete_tx::bytes [%0], [%1, {%3, %4, %4, %4, %5}], [%2];"
               ::"r"(dst), "l"(map), "r"(bar), "r"(c0), "r"(0), "r"(c4) : "memory");
}
__device__ __forceinline__ uint32_t relu_mul_bf16x2(uint32_t g, uint32_t u) {
  uint32_t r;
  asm("{\n.reg .b32 t;\nmax.NaN.bf16x2 t, %1, %3;\nmul.rn.bf16x2 %0, t, %2;\n}" : "=r"(r) : "r"(g), "r"(u), "r"(0u));
  return r;
}
__device__ __forceinline__ void team_arrive(unsigned int* ctr) {
  asm volatile("fence.acq_rel.gpu;\nred.relaxed.gpu.global.add.u32 [%0], 1;" ::"l"(ctr) : "memory");
}
__device__ __forceinline__ void st_global_v2(void* p, uint32_t a, uint32_t b) {
  asm volatile("st.global.v2.b32 [%0], {%1, %2};" ::"l"(p), "r"(a), "r"(b) : "memory");
}

template <int NSTEPS>
__device__ __forceinline__ void gemm_split_k(float (&acc)[64], uint32_t base, uint32_t bar_full, int cw, int tid XTRACE_PARAMS) {
  const uint32_t bar_empty = bar_full + 32;
#pragma unroll 1
  for (int s = 0; s < NSTEPS; s++) {
    const int st = s & 3;
    mbar_wait(bar_full + st * 8, (s >> 2) & 1);
    if ((s & 3) == 0 || s < 4) { XTRACE(0x40 + s) }
    const uint32_t sa = base + st * 49152;
    const uint32_t da = make_desc(sa + cw * 8192, 16);
    const uint32_t db = make_desc(sa + 16384 + cw * 8192, 16384);
    wgmma_fence();
#pragma unroll
    for (int i = 0; i < 4; i++) wgmma_ss_n128<1>(acc, desc_add(da, i * 32), desc_add(db, i * 2048), (s | i) != 0);
    wgmma_commit();
    if (s > 0) {
      wgmma_wait<1>();
      if (tid == 0) mbar_arrive(bar_empty + ((s - 1) & 3) * 8);
    }
  }
  wgmma_wait<0>();
  if (tid == 0) mbar_arrive(bar_empty + ((NSTEPS - 1) & 3) * 8);
  fence_regs(acc);
}

__device__ __forceinline__ void reduce_add_residual(const float (&acc)[64], const uint32_t (&res)[16], uint32_t (&pk)[16], uint32_t xbuf,
                                                    int cw, int tid) {
  const uint32_t wr = xbuf + cw * 16384 + tid * 16, rd = xbuf + (cw ^ 1) * 16384 + tid * 16;
#pragma unroll
  for (int i = 0; i < 8; i++) {
    const float v0 = cw ? acc[4 * i] : acc[32 + 4 * i], v1 = cw ? acc[4 * i + 1] : acc[32 + 4 * i + 1];
    const float v2 = cw ? acc[4 * i + 2] : acc[32 + 4 * i + 2], v3 = cw ? acc[4 * i + 3] : acc[32 + 4 * i + 3];
    asm volatile("st.shared.v4.f32 [%0], {%1, %2, %3, %4};" ::"r"(wr + i * 2048), "f"(v0), "f"(v1), "f"(v2), "f"(v3) : "memory");
  }
  bar_sync(1, 256);
#pragma unroll
  for (int i = 0; i < 8; i++) {
    float4 t;
    asm volatile("ld.shared.v4.f32 {%0, %1, %2, %3}, [%4];" : "=f"(t.x), "=f"(t.y), "=f"(t.z), "=f"(t.w) : "r"(rd + i * 2048) : "memory");
    const uint32_t p0 = pack_bf16(t.x + (cw ? acc[32 + 4 * i] : acc[4 * i]), t.y + (cw ? acc[32 + 4 * i + 1] : acc[4 * i + 1]));
    const uint32_t p1 = pack_bf16(t.z + (cw ? acc[32 + 4 * i + 2] : acc[4 * i + 2]), t.w + (cw ? acc[32 + 4 * i + 3] : acc[4 * i + 3]));
    pk[2 * i] = pack_bf16(bf_lo(p0) + bf_lo(res[2 * i]), bf_hi(p0) + bf_hi(res[2 * i]));
    pk[2 * i + 1] = pack_bf16(bf_lo(p1) + bf_lo(res[2 * i + 1]), bf_hi(p1) + bf_hi(res[2 * i + 1]));
  }
}

__global__ void __launch_bounds__(384, 1)
tail_kernel(const __grid_constant__ CUtensorMap mCtx, const __grid_constant__ CUtensorMap mWo, const __grid_constant__ CUtensorMap mH,
            const __grid_constant__ CUtensorMap mWg, const __grid_constant__ CUtensorMap mWu, const __grid_constant__ CUtensorMap mAct,
            const __grid_constant__ CUtensorMap mWd, const __grid_constant__ CUtensorMap mOut, const bf16* __restrict__ x) {
  extern __shared__ uint8_t smem_raw[];
  const uint32_t base = align1024(smem_u32(smem_raw));
  const uint32_t barC = base + TL_BARS, barD = barC + 64, barE = barD + 64;
  WATCHDOG_DECL
  if (threadIdx.x == 0) {
    for (int i = 0; i < 12; i++) {
      mbar_init(barC + (i >> 2) * 64 + (i & 3) * 8, 1);
      mbar_init(barC + (i >> 2) * 64 + 32 + (i & 3) * 8, 2);
    }
    asm volatile("fence.mbarrier_init.release.cluster;" ::: "memory");
  }
  if (threadIdx.x == 0) { PROF(2, 0) }
  __syncthreads();
  const int team = blockIdx.x >> 3, member = blockIdx.x & 7;
  const int mhalf = member >> 2, nt = member & 3;
  const int m64 = team * 2 + mhalf;
  const int n0 = member * 176;
  const int wg = threadIdx.x >> 7, warp = (threadIdx.x >> 5) & 3, lane = threadIdx.x & 31;
  if (wg == 0) {
    reg_dec<40>();
    if (warp == 0 && lane == 0) {
      auto load_wo = [&](int s) {
        const uint32_t dst = base + (s & 3) * 49152, fb = barC + (s & 3) * 8;
        mbar_expect_tx(fb, 49152);
        tma_load_2d(dst + 16384, &mWo, nt * 128, s * 128, fb);
        tma_load_2d(dst + 32768, &mWo, nt * 128 + 64, s * 128, fb);
      };
      for (int s = 0; s < 4; s++) load_wo(s);
      pdl_wait();
      for (int s = 0; s < NH; s++) {
        const uint32_t dst = base + (s & 3) * 49152, fb = barC + (s & 3) * 8;
        if (s >= 4) {
          mbar_wait(barC + 32 + (s & 3) * 8, ((s >> 2) & 1) ^ 1);
          load_wo(s);
        }
        tma_load_2d(dst, &mCtx, 0, s * SEQ + m64 * 64, fb);
        tma_load_2d(dst + 8192, &mCtx, 64, s * SEQ + m64 * 64, fb);
      }
      for (int it = 0; it < 8; it++) {
        const int st = it % 3;
        if (it < 3) {
          if (it == 0) mbar_wait(barC + 32, 1);
          mbar_wait(barC + 32 + (it + 1) * 8, 1);
        } else {
          mbar_wait(barD + 32 + st * 8, ((it / 3) & 1) ^ 1);
        }
        const uint32_t dst = base + st * 65536, fb = barD + st * 8;
        mbar_expect_tx(fb, 65536);
#pragma unroll
        for (int c = 0; c < 3; c++) {
          tma_load_5d(dst + 16384 + c * 8192, &mWg, n0 + c * 64, it * 2, fb);
          tma_load_5d(dst + 40960 + c * 8192, &mWu, n0 + c * 64, it * 2, fb);
        }
        if (it == 2) {
          spin_until(g_team + team * 2, 16);
          asm volatile("fence.proxy.async.global;" ::: "memory");
          tma_load_2d(base, &mH, 0, team * 128, barD);
          tma_load_2d(base + 65536, &mH, 64, team * 128, barD + 8);
        }
        if (it >= 2) tma_load_2d(dst, &mH, it * 64, team * 128, fb);
      }
      for (int s = 0; s < 11; s++) {
        const int st = s & 3;
        if (s < 4) {
          if (s == 0) mbar_wait(barD + 32, 0);
          if (s == 1) mbar_wait(barD + 32 + 8, 0);
          if (s == 2) mbar_wait(barD + 32 + 16, 1);
        } else {
          mbar_wait(barE + 32 + st * 8, ((s >> 2) & 1) ^ 1);
        }
        const uint32_t dst = base + st * 49152, fb = barE + st * 8;
        mbar_expect_tx(fb, 49152);
        tma_load_5d(dst + 16384, &mWd, nt * 128, s * 8, fb);
        tma_load_5d(dst + 32768, &mWd, nt * 128 + 64, s * 8, fb);
        if (s == 3) {
          spin_until(g_team + team * 2 + 1, 16);
          asm volatile("fence.proxy.async.global;" ::: "memory");
          for (int i = 0; i < 3; i++) {
            tma_load_2d(base + i * 49152, &mAct, i * 128, m64 * 64, barE + i * 8);
            tma_load_2d(base + i * 49152 + 8192, &mAct, i * 128 + 64, m64 * 64, barE + i * 8);
          }
        }
        if (s >= 3) {
          tma_load_2d(dst, &mAct, s * 128, m64 * 64, fb);
          tma_load_2d(dst + 8192, &mAct, s * 128 + 64, m64 * 64, fb);
        }
      }
    } else if (warp == 1) {
      pdl_wait();
      for (int i = lane; i < 352; i += 32) {
        const float c = __ldcg(g_cs + (i / 176) * 1408 + n0 + (i % 176));
        asm volatile("st.shared.f32 [%0], %1;" ::"r"(base + TL_CS + i * 4), "f"(c) : "memory");
      }
      bar_arrive(4, 288);
    }
    WATCHDOG_RUN(2)
  } else {
    reg_inc<232>();
    const int cw = wg - 1;
    const int tid = threadIdx.x & 127;
    const uint32_t xbuf = base + TL_XBUF;
    XTRACE_DECL(1 + cw, 2)
    uint32_t hk[16];
    const int row0 = m64 * 64 + warp * 16 + (lane >> 2);
    {
      const int col0 = nt * 128 + cw * 64 + (lane & 3) * 2;
      uint32_t res[16];
#pragma unroll
      for (int i = 0; i < 8; i++) {
        res[2 * i] = __ldg(reinterpret_cast<const uint32_t*>(x + (size_t)row0 * DM + col0 + 8 * i));
        res[2 * i + 1] = __ldg(reinterpret_cast<const uint32_t*>(x + (size_t)(row0 + 8) * DM + col0 + 8 * i));
      }
      if (tid == 0 && cw == 0) { PROF(2, 1) }
      XTRACE(1)
      float acc[64];
      gemm_split_k<NH>(acc, base, barC, cw, tid XTRACE_ARGS);
      XTRACE(2)
      reduce_add_residual(acc, res, hk, xbuf, cw, tid);
      bf16* const hp = g_h + (size_t)row0 * DM + nt * 128 + cw * 64 + (lane & 3) * 8;
#pragma unroll
      for (int a = 0; a < 2; a++) {
        st_global_v4(hp + 32 * a, hk[8 * a], hk[8 * a + 2], hk[8 * a + 4], hk[8 * a + 6]);
        st_global_v4(hp + 32 * a + 8 * DM, hk[8 * a + 1], hk[8 * a + 3], hk[8 * a + 5], hk[8 * a + 7]);
      }
      float s0 = 0.f, s1 = 0.f;
#pragma unroll
      for (int i = 0; i < 8; i++) {
        s0 += bf_lo(hk[2 * i]) + bf_hi(hk[2 * i]);
        s1 += bf_lo(hk[2 * i + 1]) + bf_hi(hk[2 * i + 1]);
      }
      s0 += __shfl_xor_sync(0xffffffffu, s0, 1); s1 += __shfl_xor_sync(0xffffffffu, s1, 1);
      s0 += __shfl_xor_sync(0xffffffffu, s0, 2); s1 += __shfl_xor_sync(0xffffffffu, s1, 2);
      const float mu0 = s0 * (1.f / 64), mu1 = s1 * (1.f / 64);
      float q0 = 0.f, q1 = 0.f;
#pragma unroll
      for (int i = 0; i < 8; i++) {
        const float a = bf_lo(hk[2 * i]) - mu0, b = bf_hi(hk[2 * i]) - mu0, c = bf_lo(hk[2 * i + 1]) - mu1, d = bf_hi(hk[2 * i + 1]) - mu1;
        q0 += a * a + b * b;
        q1 += c * c + d * d;
      }
      q0 += __shfl_xor_sync(0xffffffffu, q0, 1); q1 += __shfl_xor_sync(0xffffffffu, q1, 1);
      q0 += __shfl_xor_sync(0xffffffffu, q0, 2); q1 += __shfl_xor_sync(0xffffffffu, q1, 2);
      if ((lane & 3) == 0) {
        g_stats[row0 * 8 + nt * 2 + cw] = make_float2(mu0, q0);
        g_stats[(row0 + 8) * 8 + nt * 2 + cw] = make_float2(mu1, q1);
      }
      bar_sync(2 + cw, 128);
      if (tid == 0) team_arrive(g_team + team * 2);
      XTRACE(3)
    }
    {
      float ag[88], au[88];
      float mean[2], rstd[2];
      int st = 0, prev = 0;
      uint32_t ph = 0;
#pragma unroll 1
      for (int it = 0; it < 8; it++) {
        mbar_wait(barD + st * 8, ph);
        if (it == 0) { XTRACE(4) }
        const uint32_t sa = base + st * 65536;
        const uint32_t da = make_desc(sa + cw * 8192, 16);
        const uint32_t dg = make_desc(sa + 16384, 8192);
        const uint32_t du = make_desc(sa + 40960, 8192);
        wgmma_fence();
#pragma unroll
        for (int kk = 0; kk < 4; kk++) {
          wgmma_ss_n176<1>(ag, desc_add(da, kk * 32), desc_add(dg, kk * 2048), (it | kk) != 0);
          wgmma_ss_n176<1>(au, desc_add(da, kk * 32), desc_add(du, kk * 2048), (it | kk) != 0);
        }
        wgmma_commit();
        if (it > 0) {
          wgmma_wait<1>();
          if (tid == 0) mbar_arrive(barD + 32 + prev * 8);
        }
        prev = st;
        if (++st == 3) { st = 0; ph ^= 1; }
      }
      const int drow = team * 128 + cw * 64 + warp * 16 + (lane >> 2);
#pragma unroll
      for (int r = 0; r < 2; r++) {
        const float4* sp = reinterpret_cast<const float4*>(g_stats + (drow + 8 * r) * 8);
        const float4 a = __ldcg(sp), b = __ldcg(sp + 1), c = __ldcg(sp + 2), d = __ldcg(sp + 3);
        const float mu = (a.x + a.z + b.x + b.z + c.x + c.z + d.x + d.z) * 0.125f;
        float m2 = a.y + a.w + b.y + b.w + c.y + c.w + d.y + d.w;
        m2 += 64.f * ((a.x - mu) * (a.x - mu) + (a.z - mu) * (a.z - mu) + (b.x - mu) * (b.x - mu) + (b.z - mu) * (b.z - mu) +
                      (c.x - mu) * (c.x - mu) + (c.z - mu) * (c.z - mu) + (d.x - mu) * (d.x - mu) + (d.z - mu) * (d.z - mu));
        mean[r] = mu;
        rstd[r] = 1.f / sqrtf(m2 * (1.f / DM) + 1e-5f);
      }
      bar_sync(4, 288);
      wgmma_wait<0>();
      if (tid == 0) mbar_arrive(barD + 32 + prev * 8);
      fence_regs(ag);
      fence_regs(au);
      XTRACE(5)
      bf16* const actp = g_act + (size_t)drow * ACT_PITCH + n0 + (lane & 3) * 4;
      const uint32_t csb = base + TL_CS + (lane & 3) * 8;
#pragma unroll
      for (int j = 0; j < 11; j++) {
        uint32_t o4[4];
#pragma unroll
        for (int hh = 0; hh < 2; hh++) {
          const int i = 2 * j + hh;
          float2 cg, cu;
          asm volatile("ld.shared.v2.f32 {%0, %1}, [%2];" : "=f"(cg.x), "=f"(cg.y) : "r"(csb + i * 32) : "memory");
          asm volatile("ld.shared.v2.f32 {%0, %1}, [%2];" : "=f"(cu.x), "=f"(cu.y) : "r"(csb + 704 + i * 32) : "memory");
#pragma unroll
          for (int r = 0; r < 2; r++) {
            const uint32_t g = pack_bf16(fmaf(-mean[r], cg.x, ag[4 * i + 2 * r]) * rstd[r], fmaf(-mean[r], cg.y, ag[4 * i + 2 * r + 1]) * rstd[r]);
            const uint32_t u = pack_bf16(fmaf(-mean[r], cu.x, au[4 * i + 2 * r]) * rstd[r], fmaf(-mean[r], cu.y, au[4 * i + 2 * r + 1]) * rstd[r]);
            o4[2 * hh + r] = relu_mul_bf16x2(g, u);
          }
        }
        st_global_v2(actp + j * 16, o4[0], o4[2]);
        st_global_v2(actp + j * 16 + 8 * ACT_PITCH, o4[1], o4[3]);
      }
      XTRACE(6)
      bar_sync(2 + cw, 128);
      if (tid == 0) team_arrive(g_team + team * 2 + 1);
      XTRACE(7)
    }
    {
      float acc[64];
      gemm_split_k<11>(acc, base, barE, cw, tid XTRACE_ARGS);
      XTRACE(8)
      uint32_t pk[16];
      reduce_add_residual(acc, hk, pk, xbuf, cw, tid);
      const uint32_t mystag = xbuf + (cw ^ 1) * 16384;
      bar_sync(2 + cw, 128);
      const int row = warp * 16 + (lane & 7) + ((lane >> 3) & 1) * 8;
#pragma unroll
      for (int j = 0; j < 4; j++) {
        const int chunk = 2 * j + (lane >> 4);
        stmatrix_x4(mystag + row * 128 + ((chunk ^ (row & 7)) << 4), pk[4 * j], pk[4 * j + 1], pk[4 * j + 2], pk[4 * j + 3]);
      }
      fence_async_smem();
      bar_sync(2 + cw, 128);
      if (tid == 0) {
        tma_store_2d(&mOut, mystag, nt * 128 + cw * 64, m64 * 64);
        bulk_commit();
        bulk_wait_read<0>();
      }
      XTRACE(9)
      XTRACE_END()
    }
    if (tid == 0) { PROF(2, 2 + cw) }
    WATCHDOG_DONE()
  }
}
typedef CUresult (*EncodeTiledFn)(CUtensorMap*, CUtensorMapDataType, cuuint32_t, void*, const cuuint64_t*, const cuuint64_t*,
                                  const cuuint32_t*, const cuuint32_t*, CUtensorMapInterleave, CUtensorMapSwizzle,
                                  CUtensorMapL2promotion, CUtensorMapFloatOOBfill);

EncodeTiledFn encode_fn() {
  static EncodeTiledFn fn = nullptr;
  if (!fn) {
    void* p = nullptr;
    cudaDriverEntryPointQueryResult q;
    cudaGetDriverEntryPoint("cuTensorMapEncodeTiled", &p, cudaEnableDefault, &q);
    fn = (EncodeTiledFn)p;
  }
  return fn;
}

CUtensorMap map2d(const void* ptr, uint64_t inner, uint64_t outer, uint64_t pitch_elems, uint32_t box_inner, uint32_t box_outer,
                  CUtensorMapSwizzle sw = CU_TENSOR_MAP_SWIZZLE_128B) {
  CUtensorMap m;
  cuuint64_t dims[2] = {inner, outer};
  cuuint64_t strides[1] = {pitch_elems * 2};
  cuuint32_t box[2] = {box_inner, box_outer};
  cuuint32_t es[2] = {1, 1};
  encode_fn()(&m, CU_TENSOR_MAP_DATA_TYPE_BFLOAT16, 2, const_cast<void*>(ptr), dims, strides, box, es, CU_TENSOR_MAP_INTERLEAVE_NONE, sw,
              CU_TENSOR_MAP_L2_PROMOTION_L2_256B, CU_TENSOR_MAP_FLOAT_OOB_FILL_NONE);
  return m;
}

CUtensorMap map3d_chunks(const void* ptr, uint64_t rows, uint64_t cols, uint32_t box_rows, uint32_t chunks) {
  CUtensorMap m;
  cuuint64_t dims[3] = {64, rows, cols / 64};
  cuuint64_t strides[2] = {cols * 2, 128};
  cuuint32_t box[3] = {64, box_rows, chunks};
  cuuint32_t es[3] = {1, 1, 1};
  encode_fn()(&m, CU_TENSOR_MAP_DATA_TYPE_BFLOAT16, 3, const_cast<void*>(ptr), dims, strides, box, es, CU_TENSOR_MAP_INTERLEAVE_NONE,
              CU_TENSOR_MAP_SWIZZLE_128B, CU_TENSOR_MAP_L2_PROMOTION_L2_256B, CU_TENSOR_MAP_FLOAT_OOB_FILL_NONE);
  return m;
}

CUtensorMap map5d_perm32(const void* ptr, uint64_t rows, uint64_t cols, uint32_t groups) {
  CUtensorMap m;
  const cuuint64_t row = cols * 2;
  cuuint64_t dims[5] = {cols, 2, 4, 4, rows / 32};
  cuuint64_t strides[4] = {row, 8 * row, 2 * row, 32 * row};
  cuuint32_t box[5] = {64, 2, 4, 4, groups};
  cuuint32_t es[5] = {1, 1, 1, 1, 1};
  encode_fn()(&m, CU_TENSOR_MAP_DATA_TYPE_BFLOAT16, 5, const_cast<void*>(ptr), dims, strides, box, es, CU_TENSOR_MAP_INTERLEAVE_NONE,
              CU_TENSOR_MAP_SWIZZLE_128B, CU_TENSOR_MAP_L2_PROMOTION_L2_256B, CU_TENSOR_MAP_FLOAT_OOB_FILL_NONE);
  return m;
}
CUtensorMap map5d_perm16(const void* ptr, uint64_t rows, uint64_t cols, uint32_t groups) {
  CUtensorMap m;
  const cuuint64_t row = cols * 2;
  cuuint64_t dims[5] = {cols, 2, 2, 4, rows / 16};
  cuuint64_t strides[4] = {row, 8 * row, 2 * row, 16 * row};
  cuuint32_t box[5] = {64, 2, 2, 4, groups};
  cuuint32_t es[5] = {1, 1, 1, 1, 1};
  encode_fn()(&m, CU_TENSOR_MAP_DATA_TYPE_BFLOAT16, 5, const_cast<void*>(ptr), dims, strides, box, es, CU_TENSOR_MAP_INTERLEAVE_NONE,
              CU_TENSOR_MAP_SWIZZLE_128B, CU_TENSOR_MAP_L2_PROMOTION_L2_256B, CU_TENSOR_MAP_FLOAT_OOB_FILL_NONE);
  return m;
}

template <typename T> void* sym_addr(T& sym) {
  void* p = nullptr;
  cudaGetSymbolAddress(&p, sym);
  return p;
}

void build_schedule(AttnSched& s, int ncta) {
  static uint16_t lists[134][64];
  int cnt[134] = {0};
  float load[134] = {0};
  constexpr int GROUP = 8;
  for (int g = 0; g < NH / GROUP; g++)
    for (int qb = 15; qb >= 0; qb--)
      for (int h = g * GROUP; h < (g + 1) * GROUP; h++) {
        int best = 0;
        for (int c = 1; c < ncta; c++)
          if (load[c] < load[best]) best = c;
        lists[best][cnt[best]++] = (uint16_t)(h * 16 + qb);
        load[best] += (float)(qb + 1) + 0.3f;
      }
  int pos = 0;
  for (int c = 0; c < ncta; c++) {
    s.start[c] = pos;
    for (int i = 0; i < cnt[c]; i++) s.tile[pos++] = lists[c][i];
  }
  for (int c = ncta; c < 134; c++) s.start[c] = pos;
}

template <typename... KArgs, typename... Args>
void launch(void (*kern)(KArgs...), int grid, int smem, bool pdl, Args... args) {
  cudaLaunchConfig_t cfg = {};
  cfg.gridDim = dim3(grid);
  cfg.blockDim = dim3(384);
  cfg.dynamicSmemBytes = smem;
  cfg.stream = cudaStreamPerThread;
  cudaLaunchAttribute at[1];
  at[0].id = cudaLaunchAttributeProgrammaticStreamSerialization;
  at[0].val.programmaticStreamSerializationAllowed = 1;
  cfg.attrs = at;
  cfg.numAttrs = pdl ? 1 : 0;
  cudaLaunchKernelEx(&cfg, kern, KArgs(args)...);
}

}

#define USE_PDL true

extern "C" void kernel_launch(void* const* d_in, const int* in_sizes, int n_in, void* d_out, int out_size) {
  const bf16* x = (const bf16*)d_in[0];
  const bf16* ckv = (const bf16*)d_in[1];
  const bf16* wq = (const bf16*)d_in[2];
  const bf16* wuk = (const bf16*)d_in[3];
  const bf16* wuv = (const bf16*)d_in[4];
  const bf16* wo = (const bf16*)d_in[5];
  const bf16* wgate = (const bf16*)d_in[7];
  const bf16* wup = (const bf16*)d_in[8];
  const bf16* wdown = (const bf16*)d_in[9];
  bf16* out = (bf16*)d_out;

  static bool init = false;
  static AttnSched sched;
  static int nsm = 132;
  static void *p_xn, *p_q, *p_k, *p_v, *p_ctx, *p_h, *p_act;
  if (!init) {
    cudaFuncSetAttribute(qkv_kernel, cudaFuncAttributeMaxDynamicSharedMemorySize, KV_SMEM);
    cudaFuncSetAttribute(attn_kernel, cudaFuncAttributeMaxDynamicSharedMemorySize, AT_SMEM);
    cudaFuncSetAttribute(tail_kernel, cudaFuncAttributeMaxDynamicSharedMemorySize, TL_SMEM);
    int dev = 0;
    cudaGetDevice(&dev);
    cudaDeviceGetAttribute(&nsm, cudaDevAttrMultiProcessorCount, dev);
    if (nsm > 132) nsm = 132;
    build_schedule(sched, nsm);
    p_xn = sym_addr(g_xn); p_q = sym_addr(g_q); p_k = sym_addr(g_k); p_v = sym_addr(g_v); p_ctx = sym_addr(g_ctx); p_h = sym_addr(g_h); p_act = sym_addr(g_act);
    init = true;
  }

  const CUtensorMap mCkv = map2d(ckv, DM, SEQ, DM, 64, 128);
  const CUtensorMap mXn = map2d(p_xn, DM, SEQ, DM, 64, 128);
  const CUtensorMap mWk = map3d_chunks(wuk, DM, NH * HD, 64, 4);
  const CUtensorMap mWv = map3d_chunks(wuv, DM, NH * HD, 64, 4);
  const CUtensorMap mWq = map3d_chunks(wq, DM, NH * HD, 64, 4);
  launch(qkv_kernel, 128, KV_SMEM, false, mCkv, mXn, mWk, mWv, mWq, x, wgate, wup);

  const CUtensorMap mQ = map2d(p_q, HD, NH * SEQ, HD, 64, 128);
  const CUtensorMap mK = map2d(p_k, HD, NH * SEQ, HD, 64, 128);
  const CUtensorMap mV = map2d(p_v, HD, NH * SEQ, HD, 64, 128);
  launch(attn_kernel, nsm, AT_SMEM, USE_PDL, mQ, mK, mV, sched);

  const CUtensorMap mCtx = map2d(p_ctx, HD, NH * SEQ, HD, 64, 64);
  const CUtensorMap mWo = map2d(wo, DM, NH * HD, DM, 64, 128);
  const CUtensorMap mH = map2d(p_h, DM, SEQ, DM, 64, 128);
  const CUtensorMap mWg = map5d_perm32(wgate, DM, FF, 2);
  const CUtensorMap mWu = map5d_perm32(wup, DM, FF, 2);
  const CUtensorMap mAct = map2d(p_act, ACT_PITCH, SEQ, ACT_PITCH, 64, 64);
  const CUtensorMap mWd = map5d_perm16(wdown, FF, DM, 8);
  const CUtensorMap mOut = map2d(out, DM, SEQ, DM, 64, 64);
  launch(tail_kernel, 128, TL_SMEM, USE_PDL, mCtx, mWo, mH, mWg, mWu, mAct, mWd, mOut, x);
}
```

```cpp
#include <cuda_runtime.h>
#include <cuda_bf16.h>
#include <cuda.h>
#include <stdint.h>

namespace {

constexpr int SEQ = 2048, DM = 512, NH = 32, HD = 128, FF = 1376;
typedef __nv_bfloat16 bf16;

__device__ __align__(1024) bf16 g_xn[SEQ * DM];
__device__ __align__(1024) bf16 g_q[NH * SEQ * HD];
__device__ __align__(1024) bf16 g_k[NH * SEQ * HD];
__device__ __align__(1024) bf16 g_v[NH * SEQ * HD];
__device__ __align__(1024) bf16 g_ctx[NH * SEQ * HD];
__device__ __align__(1024) bf16 g_h[SEQ * DM];
__device__ __align__(1024) bf16 g_act[SEQ * 1408];
__device__ __align__(1024) float2 g_stats[SEQ * 8];
__device__ __align__(1024) float g_cs[2 * 1408];

__device__ unsigned int g_team[64];
__device__ unsigned int g_ln_count[16];

__device__ __forceinline__ uint32_t smem_u32(const void* p) { return (uint32_t)__cvta_generic_to_shared(p); }
__device__ __forceinline__ void mbar_init(uint32_t bar, uint32_t cnt) {
  asm volatile("mbarrier.init.shared::cta.b64 [%0], %1;" ::"r"(bar), "r"(cnt));
}
__device__ __forceinline__ void mbar_expect_tx(uint32_t bar, uint32_t bytes) {
  asm volatile("mbarrier.arrive.expect_tx.shared::cta.b64 _, [%0], %1;" ::"r"(bar), "r"(bytes) : "memory");
}
__device__ __forceinline__ void mbar_arrive(uint32_t bar) {
  asm volatile("mbarrier.arrive.shared::cta.b64 _, [%0];" ::"r"(bar) : "memory");
}
__device__ __forceinline__ void mbar_wait(uint32_t bar, uint32_t parity) {
  asm volatile(
      "{\n.reg .pred p;\n.reg .u32 c;\n"
      "mov.u32 c, 0;\n"
      "WAIT_LOOP:\n"
      "mbarrier.try_wait.parity.shared::cta.b64 p, [%0], %1;\n"
      "@p bra WAIT_DONE;\n"
      "add.u32 c, c, 1;\n"
      "setp.lt.u32 p, c, 0x400000;\n"
      "@p bra WAIT_LOOP;\n"
      "trap;\n"
      "WAIT_DONE:\n}"
      ::"r"(bar), "r"(parity) : "memory");
}
__device__ __forceinline__ uint32_t mbar_test(uint32_t bar, uint32_t parity) {
  uint32_t ok;
  asm volatile("{\n.reg .pred p;\nmbarrier.test_wait.parity.shared::cta.b64 p, [%1], %2;\nselp.u32 %0, 1, 0, p;\n}"
               : "=r"(ok) : "r"(bar), "r"(parity) : "memory");
  return ok;
}
__device__ __forceinline__ void spin_until(const unsigned int* ctr, unsigned int target) {
  asm volatile(
      "{\n.reg .pred p;\n.reg .u32 c, v;\n"
      "mov.u32 c, 0;\n"
      "SPIN_LOOP:\n"
      "ld.acquire.gpu.global.u32 v, [%0];\n"
      "setp.ge.u32 p, v, %1;\n"
      "@p bra SPIN_DONE;\n"
      "add.u32 c, c, 1;\n"
      "setp.lt.u32 p, c, 0x1000000;\n"
      "@p bra SPIN_LOOP;\n"
      "trap;\n"
      "SPIN_DONE:\n}"
      ::"l"(ctr), "r"(target) : "memory");
}
__device__ __forceinline__ void tma_load_2d(uint32_t dst, const CUtensorMap* map, int c0, int c1, uint32_t bar) {
  asm volatile("cp.async.bulk.tensor.2d.shared::cluster.global.mbarrier::complete_tx::bytes [%0], [%1, {%3, %4}], [%2];"
               ::"r"(dst), "l"(map), "r"(bar), "r"(c0), "r"(c1) : "memory");
}
__device__ __forceinline__ void tma_load_3d(uint32_t dst, const CUtensorMap* map, int c0, int c1, int c2, uint32_t bar) {
  asm volatile("cp.async.bulk.tensor.3d.shared::cluster.global.mbarrier::complete_tx::bytes [%0], [%1, {%3, %4, %5}], [%2];"
               ::"r"(dst), "l"(map), "r"(bar), "r"(c0), "r"(c1), "r"(c2) : "memory");
}
__device__ __forceinline__ void tma_store_2d(const CUtensorMap* map, uint32_t src, int c0, int c1) {
  asm volatile("cp.async.bulk.tensor.2d.global.shared::cta.bulk_group [%0, {%2, %3}], [%1];"
               ::"l"(map), "r"(src), "r"(c0), "r"(c1) : "memory");
}
__device__ __forceinline__ void tma_prefetch_desc(const CUtensorMap* map) {
  asm volatile("prefetch.tensormap [%0];" ::"l"(map) : "memory");
}
__device__ __forceinline__ void bulk_commit() { asm volatile("cp.async.bulk.commit_group;" ::: "memory"); }
template <int N> __device__ __forceinline__ void bulk_wait_read() { asm volatile("cp.async.bulk.wait_group.read %0;" ::"n"(N) : "memory"); }
template <int N> __device__ __forceinline__ void bulk_wait() { asm volatile("cp.async.bulk.wait_group %0;" ::"n"(N) : "memory"); }
__device__ __forceinline__ void fence_async_smem() { asm volatile("fence.proxy.async.shared::cta;" ::: "memory"); }
__device__ __forceinline__ void bar_sync(int id, int n) { asm volatile("bar.sync %0, %1;" ::"r"(id), "r"(n) : "memory"); }
__device__ __forceinline__ void bar_arrive(int id, int n) { asm volatile("bar.arrive %0, %1;" ::"r"(id), "r"(n) : "memory"); }
__device__ __forceinline__ void pdl_wait() { asm volatile("griddepcontrol.wait;" ::: "memory"); }
__device__ __forceinline__ void pdl_launch() { asm volatile("griddepcontrol.launch_dependents;" ::: "memory"); }
template <int N> __device__ __forceinline__ void reg_inc() { asm volatile("setmaxnreg.inc.sync.aligned.u32 %0;" ::"n"(N)); }
template <int N> __device__ __forceinline__ void reg_dec() { asm volatile("setmaxnreg.dec.sync.aligned.u32 %0;" ::"n"(N)); }
__device__ __forceinline__ void wgmma_fence() { asm volatile("wgmma.fence.sync.aligned;" ::: "memory"); }
__device__ __forceinline__ void wgmma_commit() { asm volatile("wgmma.commit_group.sync.aligned;" ::: "memory"); }
template <int N> __device__ __forceinline__ void wgmma_wait() { asm volatile("wgmma.wait_group.sync.aligned %0;" ::"n"(N) : "memory"); }
template <int N> __device__ __forceinline__ void fence_regs(float (&r)[N]) {
#pragma unroll
  for (int i = 0; i < N; i++) asm volatile("" : "+f"(r[i])::"memory");
}
template <int N> __device__ __forceinline__ void fence_regs(uint32_t (&r)[N]) {
#pragma unroll
  for (int i = 0; i < N; i++) asm volatile("" : "+r"(r[i])::"memory");
}
__device__ __forceinline__ uint32_t make_desc(uint32_t addr, uint32_t lbo_bytes) { return ((addr & 0x3FFFF) >> 4) | ((lbo_bytes >> 4) << 16); }
__device__ __forceinline__ uint32_t desc_add(uint32_t d, uint32_t bytes) { return d + (bytes >> 4); }
__device__ __forceinline__ uint32_t pack_bf16(float lo, float hi) {
  uint32_t r;
  asm("cvt.rn.bf16x2.f32 %0, %1, %2;" : "=r"(r) : "f"(hi), "f"(lo));
  return r;
}
__device__ __forceinline__ float bf_lo(uint32_t v) { return __uint_as_float(v << 16); }
__device__ __forceinline__ float bf_hi(uint32_t v) { return __uint_as_float(v & 0xffff0000u); }
__device__ __forceinline__ float ex2(float x) {
  float y;
  asm("ex2.approx.ftz.f32 %0, %1;" : "=f"(y) : "f"(x));
  return y;
}
__device__ __forceinline__ void stmatrix_x4(uint32_t addr, uint32_t a, uint32_t b, uint32_t c, uint32_t d) {
  asm volatile("stmatrix.sync.aligned.m8n8.x4.shared.b16 [%0], {%1, %2, %3, %4};"
               ::"r"(addr), "r"(a), "r"(b), "r"(c), "r"(d) : "memory");
}
__device__ __forceinline__ uint32_t align1024(uint32_t a) { return (a + 1023u) & ~1023u; }

template <int TB>
__device__ __forceinline__ void wgmma_ss_n128(float (&d)[64], uint32_t da, uint32_t db, int scale_d) {
  asm volatile("{\n.reg .pred p;\n.reg .b64 da, db;\nsetp.ne.b32 p, %66, 0;\nmov.b64 da, {%64, 0x40000040};\nmov.b64 db, {%65, 0x40000040};\n"
    "wgmma.mma_async.sync.aligned.m64n128k16.f32.bf16.bf16 "
    "{%0, %1, %2, %3, %4, %5, %6, %7, %8, %9, %10, %11, %12, %13, %14, %15, "
    "%16, %17, %18, %19, %20, %21, %22, %23, %24, %25, %26, %27, %28, %29, %30, %31, "
    "%32, %33, %34, %35, %36, %37, %38, %39, %40, %41, %42, %43, %44, %45, %46, %47, "
    "%48, %49, %50, %51, %52, %53, %54, %55, %56, %57, %58, %59, %60, %61, %62, %63}, "
    "da, db, p, 1, 1, 0, %67;\n}\n"
    :
      "+f"(d[0]), "+f"(d[1]), "+f"(d[2]), "+f"(d[3]), "+f"(d[4]), "+f"(d[5]), "+f"(d[6]), "+f"(d[7]),
      "+f"(d[8]), "+f"(d[9]), "+f"(d[10]), "+f"(d[11]), "+f"(d[12]), "+f"(d[13]), "+f"(d[14]), "+f"(d[15]),
      "+f"(d[16]), "+f"(d[17]), "+f"(d[18]), "+f"(d[19]), "+f"(d[20]), "+f"(d[21]), "+f"(d[22]), "+f"(d[23]),
      "+f"(d[24]), "+f"(d[25]), "+f"(d[26]), "+f"(d[27]), "+f"(d[28]), "+f"(d[29]), "+f"(d[30]), "+f"(d[31]),
      "+f"(d[32]), "+f"(d[33]), "+f"(d[34]), "+f"(d[35]), "+f"(d[36]), "+f"(d[37]), "+f"(d[38]), "+f"(d[39]),
      "+f"(d[40]), "+f"(d[41]), "+f"(d[42]), "+f"(d[43]), "+f"(d[44]), "+f"(d[45]), "+f"(d[46]), "+f"(d[47]),
      "+f"(d[48]), "+f"(d[49]), "+f"(d[50]), "+f"(d[51]), "+f"(d[52]), "+f"(d[53]), "+f"(d[54]), "+f"(d[55]),
      "+f"(d[56]), "+f"(d[57]), "+f"(d[58]), "+f"(d[59]), "+f"(d[60]), "+f"(d[61]), "+f"(d[62]), "+f"(d[63])
    : "r"(da), "r"(db), "r"(scale_d), "n"(TB));
}
template <int TB>
__device__ __forceinline__ void wgmma_rs_n128(float (&d)[64], uint32_t a0, uint32_t a1, uint32_t a2, uint32_t a3, uint32_t db, int scale_d) {
  asm volatile("{\n.reg .pred p;\n.reg .b64 db;\nsetp.ne.b32 p, %69, 0;\nmov.b64 db, {%68, 0x40000040};\n"
    "wgmma.mma_async.sync.aligned.m64n128k16.f32.bf16.bf16 "
    "{%0, %1, %2, %3, %4, %5, %6, %7, %8, %9, %10, %11, %12, %13, %14, %15, "
    "%16, %17, %18, %19, %20, %21, %22, %23, %24, %25, %26, %27, %28, %29, %30, %31, "
    "%32, %33, %34, %35, %36, %37, %38, %39, %40, %41, %42, %43, %44, %45, %46, %47, "
    "%48, %49, %50, %51, %52, %53, %54, %55, %56, %57, %58, %59, %60, %61, %62, %63}, "
    "{%64, %65, %66, %67}, db, p, 1, 1, %70;\n}\n"
    :
      "+f"(d[0]), "+f"(d[1]), "+f"(d[2]), "+f"(d[3]), "+f"(d[4]), "+f"(d[5]), "+f"(d[6]), "+f"(d[7]),
      "+f"(d[8]), "+f"(d[9]), "+f"(d[10]), "+f"(d[11]), "+f"(d[12]), "+f"(d[13]), "+f"(d[14]), "+f"(d[15]),
      "+f"(d[16]), "+f"(d[17]), "+f"(d[18]), "+f"(d[19]), "+f"(d[20]), "+f"(d[21]), "+f"(d[22]), "+f"(d[23]),
      "+f"(d[24]), "+f"(d[25]), "+f"(d[26]), "+f"(d[27]), "+f"(d[28]), "+f"(d[29]), "+f"(d[30]), "+f"(d[31]),
      "+f"(d[32]), "+f"(d[33]), "+f"(d[34]), "+f"(d[35]), "+f"(d[36]), "+f"(d[37]), "+f"(d[38]), "+f"(d[39]),
      "+f"(d[40]), "+f"(d[41]), "+f"(d[42]), "+f"(d[43]), "+f"(d[44]), "+f"(d[45]), "+f"(d[46]), "+f"(d[47]),
      "+f"(d[48]), "+f"(d[49]), "+f"(d[50]), "+f"(d[51]), "+f"(d[52]), "+f"(d[53]), "+f"(d[54]), "+f"(d[55]),
      "+f"(d[56]), "+f"(d[57]), "+f"(d[58]), "+f"(d[59]), "+f"(d[60]), "+f"(d[61]), "+f"(d[62]), "+f"(d[63])
    : "r"(a0), "r"(a1), "r"(a2), "r"(a3), "r"(db), "r"(scale_d), "n"(TB));
}
template <int TB>
__device__ __forceinline__ void wgmma_ss_n176(float (&d)[88], uint32_t da, uint32_t db, int scale_d) {
  asm volatile("{\n.reg .pred p;\n.reg .b64 da, db;\nsetp.ne.b32 p, %90, 0;\nmov.b64 da, {%88, 0x40000040};\nmov.b64 db, {%89, 0x40000040};\n"
    "wgmma.mma_async.sync.aligned.m64n176k16.f32.bf16.bf16 "
    "{%0, %1, %2, %3, %4, %5, %6, %7, %8, %9, %10, %11, %12, %13, %14, %15, "
    "%16, %17, %18, %19, %20, %21, %22, %23, %24, %25, %26, %27, %28, %29, %30, %31, "
    "%32, %33, %34, %35, %36, %37, %38, %39, %40, %41, %42, %43, %44, %45, %46, %47, "
    "%48, %49, %50, %51, %52, %53, %54, %55, %56, %57, %58, %59, %60, %61, %62, %63, "
    "%64, %65, %66, %67, %68, %69, %70, %71, %72, %73, %74, %75, %76, %77, %78, %79, "
    "%80, %81, %82, %83, %84, %85, %86, %87}, "
    "da, db, p, 1, 1, 0, %91;\n}\n"
    :
      "+f"(d[0]), "+f"(d[1]), "+f"(d[2]), "+f"(d[3]), "+f"(d[4]), "+f"(d[5]), "+f"(d[6]), "+f"(d[7]),
      "+f"(d[8]), "+f"(d[9]), "+f"(d[10]), "+f"(d[11]), "+f"(d[12]), "+f"(d[13]), "+f"(d[14]), "+f"(d[15]),
      "+f"(d[16]), "+f"(d[17]), "+f"(d[18]), "+f"(d[19]), "+f"(d[20]), "+f"(d[21]), "+f"(d[22]), "+f"(d[23]),
      "+f"(d[24]), "+f"(d[25]), "+f"(d[26]), "+f"(d[27]), "+f"(d[28]), "+f"(d[29]), "+f"(d[30]), "+f"(d[31]),
      "+f"(d[32]), "+f"(d[33]), "+f"(d[34]), "+f"(d[35]), "+f"(d[36]), "+f"(d[37]), "+f"(d[38]), "+f"(d[39]),
      "+f"(d[40]), "+f"(d[41]), "+f"(d[42]), "+f"(d[43]), "+f"(d[44]), "+f"(d[45]), "+f"(d[46]), "+f"(d[47]),
      "+f"(d[48]), "+f"(d[49]), "+f"(d[50]), "+f"(d[51]), "+f"(d[52]), "+f"(d[53]), "+f"(d[54]), "+f"(d[55]),
      "+f"(d[56]), "+f"(d[57]), "+f"(d[58]), "+f"(d[59]), "+f"(d[60]), "+f"(d[61]), "+f"(d[62]), "+f"(d[63]),
      "+f"(d[64]), "+f"(d[65]), "+f"(d[66]), "+f"(d[67]), "+f"(d[68]), "+f"(d[69]), "+f"(d[70]), "+f"(d[71]),
      "+f"(d[72]), "+f"(d[73]), "+f"(d[74]), "+f"(d[75]), "+f"(d[76]), "+f"(d[77]), "+f"(d[78]), "+f"(d[79]),
      "+f"(d[80]), "+f"(d[81]), "+f"(d[82]), "+f"(d[83]), "+f"(d[84]), "+f"(d[85]), "+f"(d[86]), "+f"(d[87])
    : "r"(da), "r"(db), "r"(scale_d), "n"(TB));
}
template <int TB>
__device__ __forceinline__ void wgmma_ss_n256(float (&d)[128], uint32_t da, uint32_t db, int scale_d) {
  asm volatile("{\n.reg .pred p;\n.reg .b64 da, db;\nsetp.ne.b32 p, %130, 0;\nmov.b64 da, {%128, 0x40000040};\nmov.b64 db, {%129, 0x40000040};\n"
    "wgmma.mma_async.sync.aligned.m64n256k16.f32.bf16.bf16 "
    "{%0, %1, %2, %3, %4, %5, %6, %7, %8, %9, %10, %11, %12, %13, %14, %15, "
    "%16, %17, %18, %19, %20, %21, %22, %23, %24, %25, %26, %27, %28, %29, %30, %31, "
    "%32, %33, %34, %35, %36, %37, %38, %39, %40, %41, %42, %43, %44, %45, %46, %47, "
    "%48, %49, %50, %51, %52, %53, %54, %55, %56, %57, %58, %59, %60, %61, %62, %63, "
    "%64, %65, %66, %67, %68, %69, %70, %71, %72, %73, %74, %75, %76, %77, %78, %79, "
    "%80, %81, %82, %83, %84, %85, %86, %87, %88, %89, %90, %91, %92, %93, %94, %95, "
    "%96, %97, %98, %99, %100, %101, %102, %103, %104, %105, %106, %107, %108, %109, %110, %111, "
    "%112, %113, %114, %115, %116, %117, %118, %119, %120, %121, %122, %123, %124, %125, %126, %127}, "
    "da, db, p, 1, 1, 0, %131;\n}\n"
    :
      "+f"(d[0]), "+f"(d[1]), "+f"(d[2]), "+f"(d[3]), "+f"(d[4]), "+f"(d[5]), "+f"(d[6]), "+f"(d[7]),
      "+f"(d[8]), "+f"(d[9]), "+f"(d[10]), "+f"(d[11]), "+f"(d[12]), "+f"(d[13]), "+f"(d[14]), "+f"(d[15]),
      "+f"(d[16]), "+f"(d[17]), "+f"(d[18]), "+f"(d[19]), "+f"(d[20]), "+f"(d[21]), "+f"(d[22]), "+f"(d[23]),
      "+f"(d[24]), "+f"(d[25]), "+f"(d[26]), "+f"(d[27]), "+f"(d[28]), "+f"(d[29]), "+f"(d[30]), "+f"(d[31]),
      "+f"(d[32]), "+f"(d[33]), "+f"(d[34]), "+f"(d[35]), "+f"(d[36]), "+f"(d[37]), "+f"(d[38]), "+f"(d[39]),
      "+f"(d[40]), "+f"(d[41]), "+f"(d[42]), "+f"(d[43]), "+f"(d[44]), "+f"(d[45]), "+f"(d[46]), "+f"(d[47]),
      "+f"(d[48]), "+f"(d[49]), "+f"(d[50]), "+f"(d[51]), "+f"(d[52]), "+f"(d[53]), "+f"(d[54]), "+f"(d[55]),
      "+f"(d[56]), "+f"(d[57]), "+f"(d[58]), "+f"(d[59]), "+f"(d[60]), "+f"(d[61]), "+f"(d[62]), "+f"(d[63]),
      "+f"(d[64]), "+f"(d[65]), "+f"(d[66]), "+f"(d[67]), "+f"(d[68]), "+f"(d[69]), "+f"(d[70]), "+f"(d[71]),
      "+f"(d[72]), "+f"(d[73]), "+f"(d[74]), "+f"(d[75]), "+f"(d[76]), "+f"(d[77]), "+f"(d[78]), "+f"(d[79]),
      "+f"(d[80]), "+f"(d[81]), "+f"(d[82]), "+f"(d[83]), "+f"(d[84]), "+f"(d[85]), "+f"(d[86]), "+f"(d[87]),
      "+f"(d[88]), "+f"(d[89]), "+f"(d[90]), "+f"(d[91]), "+f"(d[92]), "+f"(d[93]), "+f"(d[94]), "+f"(d[95]),
      "+f"(d[96]), "+f"(d[97]), "+f"(d[98]), "+f"(d[99]), "+f"(d[100]), "+f"(d[101]), "+f"(d[102]), "+f"(d[103]),
      "+f"(d[104]), "+f"(d[105]), "+f"(d[106]), "+f"(d[107]), "+f"(d[108]), "+f"(d[109]), "+f"(d[110]), "+f"(d[111]),
      "+f"(d[112]), "+f"(d[113]), "+f"(d[114]), "+f"(d[115]), "+f"(d[116]), "+f"(d[117]), "+f"(d[118]), "+f"(d[119]),
      "+f"(d[120]), "+f"(d[121]), "+f"(d[122]), "+f"(d[123]), "+f"(d[124]), "+f"(d[125]), "+f"(d[126]), "+f"(d[127])
    : "r"(da), "r"(db), "r"(scale_d), "n"(TB));
}
constexpr int KV_STAGES = 4;
constexpr int KV_STAGE_BYTES = 16384 + 32768;
constexpr int KV_SMEM = KV_STAGES * KV_STAGE_BYTES + 1024 + 256;

__device__ __forceinline__ void st_global_v4(void* p, uint32_t a, uint32_t b, uint32_t c, uint32_t d) {
  asm volatile("st.global.v4.b32 [%0], {%1, %2, %3, %4};" ::"l"(p), "r"(a), "r"(b), "r"(c), "r"(d) : "memory");
}

__device__ __forceinline__ int tile_matrix(int t, int c) { return (t == 2 || t == 5) ? 2 : (c >> 2); }
__device__ __forceinline__ int tile_pair(int t, int c) {
  if (t == 2) return 8 + c;
  if (t == 5) return c;
  const int group = t == 0 ? 3 : t == 1 ? 2 : t == 3 ? 1 : 0;
  return group * 4 + (c & 3);
}

__global__ void __launch_bounds__(384, 1)
qkv_kernel(const __grid_constant__ CUtensorMap mCkv, const __grid_constant__ CUtensorMap mXn, const __grid_constant__ CUtensorMap mWk,
           const __grid_constant__ CUtensorMap mWv, const __grid_constant__ CUtensorMap mWq, const bf16* __restrict__ x,
           const bf16* __restrict__ w_gate, const bf16* __restrict__ w_up) {
  extern __shared__ uint8_t smem_raw[];
  const uint32_t base = align1024(smem_u32(smem_raw));
  const uint32_t bars = base + KV_STAGES * KV_STAGE_BYTES;
  if (threadIdx.x == 0) {
    for (int i = 0; i < KV_STAGES; i++) {
      mbar_init(bars + i * 8, 1);
      mbar_init(bars + 64 + i * 8, 2);
    }
    asm volatile("fence.mbarrier_init.release.cluster;" ::: "memory");
  }
  if (threadIdx.x == 32) {
    tma_prefetch_desc(&mCkv);
    tma_prefetch_desc(&mWk);
    tma_prefetch_desc(&mWv);
    tma_prefetch_desc(&mXn);
    tma_prefetch_desc(&mWq);
  }
  if (blockIdx.x == 0 && threadIdx.x < 64) g_team[threadIdx.x] = 0;
  __syncthreads();
  pdl_launch();
  const int mblk = blockIdx.x & 15, ngrp = blockIdx.x >> 4;
  const int wg = threadIdx.x >> 7, warp = (threadIdx.x >> 5) & 3, lane = threadIdx.x & 31;
  if (wg == 0) {
    reg_dec<56>();
    if (warp == 0) {
      if (lane == 0) {
        for (int it = 0; it < 48; it++) {
          const int t = it >> 3, k = it & 7, st = it & 3;
          const int mat = tile_matrix(t, ngrp), pair = tile_pair(t, ngrp);
          if (it == 16) {
            spin_until(g_ln_count + mblk, 24);
            asm volatile("fence.proxy.async.global;" ::: "memory");
          }
          mbar_wait(bars + 64 + st * 8, ((it >> 2) & 1) ^ 1);
          const uint32_t sa = base + st * KV_STAGE_BYTES;
          mbar_expect_tx(bars + st * 8, KV_STAGE_BYTES);
          tma_load_2d(sa, mat == 2 ? &mXn : &mCkv, k * 64, mblk * 128, bars + st * 8);
          tma_load_3d(sa + 16384, mat == 0 ? &mWk : mat == 1 ? &mWv : &mWq, 0, k * 64, pair * 4, bars + st * 8);
        }
      }
    } else {
      {
        auto ld = [&](int r, uint4& v0, uint4& v1) {
          const uint4* src = reinterpret_cast<const uint4*>(x + (size_t)(blockIdx.x * 16 + r) * DM);
          v0 = __ldg(src + lane);
          v1 = __ldg(src + 32 + lane);
        };
        uint4 a0, a1, b0, b1;
        int r = warp - 1;
        ld(r, a0, a1);
        ld(r + 3, b0, b1);
        for (; r < 16; r += 3) {
          const uint32_t u[8] = {a0.x, a0.y, a0.z, a0.w, a1.x, a1.y, a1.z, a1.w};
          a0 = b0;
          a1 = b1;
          if (r + 6 < 16) ld(r + 6, b0, b1);
          float f[16];
          float s = 0.f;
#pragma unroll
          for (int i = 0; i < 8; i++) { f[2 * i] = bf_lo(u[i]); f[2 * i + 1] = bf_hi(u[i]); s += f[2 * i] + f[2 * i + 1]; }
#pragma unroll
          for (int o = 16; o > 0; o >>= 1) s += __shfl_xor_sync(0xffffffffu, s, o);
          const float mean = s * (1.f / DM);
          float q = 0.f;
#pragma unroll
          for (int i = 0; i < 16; i++) { f[i] -= mean; q += f[i] * f[i]; }
#pragma unroll
          for (int o = 16; o > 0; o >>= 1) q += __shfl_xor_sync(0xffffffffu, q, o);
          const float rstd = (0.08838834764831845f * 1.4426950408889634f) / sqrtf(q * (1.f / DM) + 1e-5f);
          uint4* dst = reinterpret_cast<uint4*>(g_xn + (size_t)(blockIdx.x * 16 + r) * DM);
          dst[lane] = make_uint4(pack_bf16(f[0] * rstd, f[1] * rstd), pack_bf16(f[2] * rstd, f[3] * rstd),
                                 pack_bf16(f[4] * rstd, f[5] * rstd), pack_bf16(f[6] * rstd, f[7] * rstd));
          dst[32 + lane] = make_uint4(pack_bf16(f[8] * rstd, f[9] * rstd), pack_bf16(f[10] * rstd, f[11] * rstd),
                                      pack_bf16(f[12] * rstd, f[13] * rstd), pack_bf16(f[14] * rstd, f[15] * rstd));
        }
      }
      __threadfence();
      __syncwarp();
      if (lane == 0) atomicAdd(g_ln_count + (blockIdx.x >> 3), 1u);
      const int task = blockIdx.x * 3 + (warp - 1);
      if (task < 352) {
        const int mat = task / 176, grp = task % 176;
        float a[8];
#pragma unroll
        for (int i = 0; i < 8; i++) a[i] = 0.f;
        if (grp < FF / 8) {
          const bf16* w = (mat ? w_up : w_gate) + grp * 8;
#pragma unroll 4
          for (int r = lane; r < DM; r += 32) {
            const uint4 v = __ldg(reinterpret_cast<const uint4*>(w + (size_t)r * FF));
            a[0] += bf_lo(v.x); a[1] += bf_hi(v.x); a[2] += bf_lo(v.y); a[3] += bf_hi(v.y);
            a[4] += bf_lo(v.z); a[5] += bf_hi(v.z); a[6] += bf_lo(v.w); a[7] += bf_hi(v.w);
          }
#pragma unroll
          for (int i = 0; i < 8; i++)
#pragma unroll
            for (int o = 16; o > 0; o >>= 1) a[i] += __shfl_xor_sync(0xffffffffu, a[i], o);
        }
        if (lane == 0) {
          float4* dst = reinterpret_cast<float4*>(g_cs + mat * 1408 + grp * 8);
          dst[0] = make_float4(a[0], a[1], a[2], a[3]);
          dst[1] = make_float4(a[4], a[5], a[6], a[7]);
        }
      }
    }
  } else {
    reg_inc<224>();
    const int cw = wg - 1;
    const int tid = threadIdx.x & 127;
    if (cw == 1) bar_arrive(1, 256);
    float acc[128];
    uint32_t pk[64];

    const size_t thr_off = (size_t)(mblk * 128 + cw * 64 + warp * 16 + (lane >> 2)) * HD + (lane & 3) * 8;
    bf16* prev_out = nullptr;
    auto store_piece = [&](int i) {
      bf16* dst = prev_out + (size_t)(i >> 2) * SEQ * HD + (i & 3) * 32;
      st_global_v4(dst, pk[8 * i], pk[8 * i + 2], pk[8 * i + 4], pk[8 * i + 6]);
      st_global_v4(dst + 8 * HD, pk[8 * i + 1], pk[8 * i + 3], pk[8 * i + 5], pk[8 * i + 7]);
    };
    for (int t = 0; t < 6; t++) {
#pragma unroll
      for (int k = 0; k < 8; k++) {
        const int st = k & 3;
        mbar_wait(bars + st * 8, (k >> 2) & 1);
        const uint32_t sa = base + st * KV_STAGE_BYTES;
        const uint32_t da = make_desc(sa + cw * 8192, 16);
        const uint32_t db = make_desc(sa + 16384, 8192);
        bar_sync(1 + cw, 256);
        wgmma_fence();
#pragma unroll
        for (int kk = 0; kk < 4; kk++) wgmma_ss_n256<1>(acc, desc_add(da, kk * 32), desc_add(db, kk * 2048), (k | kk) != 0);
        wgmma_commit();
        bar_arrive(2 - cw, 256);
        if (t > 0) store_piece(k);
        if (k > 0) {
          wgmma_wait<1>();
          if (tid == 0) mbar_arrive(bars + 64 + ((k - 1) & 3) * 8);
        }
      }
      wgmma_wait<0>();
      if (tid == 0) mbar_arrive(bars + 64 + 3 * 8);
      fence_regs(acc);
      const int mat = tile_matrix(t, ngrp);
#pragma unroll
      for (int i = 0; i < 64; i++) pk[i] = pack_bf16(acc[2 * i], acc[2 * i + 1]);
      prev_out = (mat == 0 ? g_k : mat == 1 ? g_v : g_q) + thr_off + (size_t)(tile_pair(t, ngrp) * 2) * SEQ * HD;
    }
#pragma unroll
    for (int i = 0; i < 8; i++) store_piece(i);
  }
}
constexpr int AT_SLOTS = 7;
constexpr int AT_SMEM = AT_SLOTS * 32768 + 1024 + 256;
struct AttnSched {
  int start[134];
  int tile[NH * 16];
};

struct RingPos {
  int slot;
  uint32_t phase;
  __device__ __forceinline__ void next() {
    if (++slot == AT_SLOTS) { slot = 0; phase ^= 1; }
  }
};

constexpr float SM_ZERO = 32.f;
constexpr float SM_LIMIT = 1099511627776.f;

template <int NG, bool SUB>
__device__ __forceinline__ void exp_pack(const float (&s)[64], uint32_t (&p)[32], float m0, float m1, float& r0, float& r1) {
  float a0 = 0.f, a1 = 0.f, b0 = 0.f, b1 = 0.f;
#pragma unroll
  for (int i = 0; i < NG; i++) {
    const float e0 = ex2(SUB ? s[4 * i] - m0 : s[4 * i]), e1 = ex2(SUB ? s[4 * i + 1] - m0 : s[4 * i + 1]);
    const float e2 = ex2(SUB ? s[4 * i + 2] - m1 : s[4 * i + 2]), e3 = ex2(SUB ? s[4 * i + 3] - m1 : s[4 * i + 3]);
    a0 += e0;
    b0 += e1;
    a1 += e2;
    b1 += e3;
    p[2 * i] = pack_bf16(e0, e1);
    p[2 * i + 1] = pack_bf16(e2, e3);
  }
#pragma unroll
  for (int i = 2 * NG; i < 32; i++) p[i] = 0u;
  r0 = a0 + b0;
  r1 = a1 + b1;
}

__device__ __forceinline__ void refresh_max(const float (&s)[64], float (&o)[64], float& m0, float& m1, float& l0, float& l1) {
  float a0 = fmaxf(s[0], s[1]), a1 = fmaxf(s[2], s[3]), b0 = fmaxf(s[4], s[5]), b1 = fmaxf(s[6], s[7]);
#pragma unroll
  for (int i = 2; i < 16; i += 2) {
    a0 = fmaxf(a0, fmaxf(s[4 * i], s[4 * i + 1]));
    a1 = fmaxf(a1, fmaxf(s[4 * i + 2], s[4 * i + 3]));
    b0 = fmaxf(b0, fmaxf(s[4 * i + 4], s[4 * i + 5]));
    b1 = fmaxf(b1, fmaxf(s[4 * i + 6], s[4 * i + 7]));
  }
  a0 = fmaxf(a0, b0);
  a1 = fmaxf(a1, b1);
  a0 = fmaxf(a0, __shfl_xor_sync(0xffffffffu, a0, 1));
  a1 = fmaxf(a1, __shfl_xor_sync(0xffffffffu, a1, 1));
  a0 = fmaxf(a0, __shfl_xor_sync(0xffffffffu, a0, 2));
  a1 = fmaxf(a1, __shfl_xor_sync(0xffffffffu, a1, 2));
  a0 = fmaxf(a0, m0);
  a1 = fmaxf(a1, m1);
  const float sc0 = ex2(m0 - a0), sc1 = ex2(m1 - a1);
  m0 = a0;
  m1 = a1;
  l0 *= sc0;
  l1 *= sc1;
#pragma unroll
  for (int i = 0; i < 16; i++) {
    o[4 * i] *= sc0;
    o[4 * i + 1] *= sc0;
    o[4 * i + 2] *= sc1;
    o[4 * i + 3] *= sc1;
  }
}

__device__ __forceinline__ void mask_diag(float (&s)[64], int cw, int warp, int lane) {
  const int t0 = cw * 64 + warp * 16 + (lane >> 2) - (lane & 3) * 2;
#pragma unroll
  for (int i = 0; i < 16; i++) {
    if (8 * i > t0) s[4 * i] = -INFINITY;
    if (8 * i + 1 > t0) s[4 * i + 1] = -INFINITY;
    if (8 * (i - 1) > t0) s[4 * i + 2] = -INFINITY;
    if (8 * (i - 1) + 1 > t0) s[4 * i + 3] = -INFINITY;
  }
}

__device__ __forceinline__ void load_q_frags(uint32_t (&q)[32], uint32_t sq, int cw, int warp, int lane) {
  const int row = cw * 64 + warp * 16 + (lane & 7) + ((lane >> 3) & 1) * 8;
  const uint32_t rbase = sq + row * 128;
#pragma unroll
  for (int j = 0; j < 8; j++) {
    const int chunk = (2 * j + (lane >> 4)) & 7;
    asm volatile("ldmatrix.sync.aligned.m8n8.x4.shared.b16 {%0, %1, %2, %3}, [%4];"
                 : "=r"(q[4 * j]), "=r"(q[4 * j + 1]), "=r"(q[4 * j + 2]), "=r"(q[4 * j + 3])
                 : "r"(rbase + (j >> 2) * 16384 + ((chunk ^ (row & 7)) << 4)) : "memory");
  }
}

__device__ __forceinline__ void row_recip(float l0, float l1, float& i0, float& i1) {
  l0 += __shfl_xor_sync(0xffffffffu, l0, 1);
  l1 += __shfl_xor_sync(0xffffffffu, l1, 1);
  l0 += __shfl_xor_sync(0xffffffffu, l0, 2);
  l1 += __shfl_xor_sync(0xffffffffu, l1, 2);
  asm("rcp.approx.ftz.f32 %0, %1;" : "=f"(i0) : "f"(l0));
  asm("rcp.approx.ftz.f32 %0, %1;" : "=f"(i1) : "f"(l1));
}
__device__ __forceinline__ void write_ctx(const float (&o)[64], float i0, float i1, bf16* dst) {
#pragma unroll
  for (int a = 0; a < 4; a++) {
    st_global_v4(dst + 32 * a, pack_bf16(o[16 * a] * i0, o[16 * a + 1] * i0), pack_bf16(o[16 * a + 4] * i0, o[16 * a + 5] * i0),
                 pack_bf16(o[16 * a + 8] * i0, o[16 * a + 9] * i0), pack_bf16(o[16 * a + 12] * i0, o[16 * a + 13] * i0));
    st_global_v4(dst + 32 * a + 8 * HD, pack_bf16(o[16 * a + 2] * i1, o[16 * a + 3] * i1), pack_bf16(o[16 * a + 6] * i1, o[16 * a + 7] * i1),
                 pack_bf16(o[16 * a + 10] * i1, o[16 * a + 11] * i1), pack_bf16(o[16 * a + 14] * i1, o[16 * a + 15] * i1));
  }
}

__global__ void __launch_bounds__(384, 1)
attn_kernel(const __grid_constant__ CUtensorMap mQ, const __grid_constant__ CUtensorMap mK, const __grid_constant__ CUtensorMap mV,
            const __grid_constant__ AttnSched sched) {
  extern __shared__ uint8_t smem_raw[];
  const uint32_t base = align1024(smem_u32(smem_raw));
  const uint32_t bar_full = base + AT_SLOTS * 32768, bar_empty = bar_full + 64;
  if (threadIdx.x == 0) {
    for (int i = 0; i < AT_SLOTS; i++) {
      mbar_init(bar_full + i * 8, 1);
      mbar_init(bar_empty + i * 8, 8);
    }
    asm volatile("fence.mbarrier_init.release.cluster;" ::: "memory");
  }
  if (threadIdx.x == 32) {
    tma_prefetch_desc(&mQ);
    tma_prefetch_desc(&mK);
    tma_prefetch_desc(&mV);
  }
  __syncthreads();
  pdl_launch();
  const int wg = threadIdx.x >> 7, warp = (threadIdx.x >> 5) & 3, lane = threadIdx.x & 31;
  const int t_begin = sched.start[blockIdx.x], t_end = sched.start[blockIdx.x + 1];
  if (wg == 0) {
    reg_dec<24>();
    if (warp == 0 && lane == 0) {
      RingPos rp{0, 1};
      auto load = [&](const CUtensorMap* m, int row) {
        mbar_wait(bar_empty + rp.slot * 8, rp.phase);
        const uint32_t dst = base + rp.slot * 32768, fb = bar_full + rp.slot * 8;
        mbar_expect_tx(fb, 32768);
        tma_load_2d(dst, m, 0, row, fb);
        tma_load_2d(dst + 16384, m, 64, row, fb);
        rp.next();
      };
      pdl_wait();
      int prev_v = -1;
      for (int ti = t_begin; ti < t_end; ti++) {
        const int tile = sched.tile[ti], h = tile >> 4, qb = tile & 15;
        if (ti == t_begin) load(&mQ, h * SEQ + qb * 128);
        for (int j = qb; j >= 0; j--) {
          if (prev_v >= 0) load(&mV, prev_v);
          load(&mK, h * SEQ + j * 128);
          if (prev_v < 0) mbar_wait(bar_full + 8, 0);
          prev_v = h * SEQ + j * 128;
          if (j == 0 && ti + 1 < t_end) {
            const int nt = sched.tile[ti + 1];
            load(&mQ, (nt >> 4) * SEQ + (nt & 15) * 128);
          }
        }
      }
      if (prev_v >= 0) load(&mV, prev_v);
    }
  } else {
    reg_inc<240>();
    const int cw = wg - 1;
    const int tid = threadIdx.x & 127;
    RingPos rp{0, 0};
    auto take = [&](int& slot) {
      mbar_wait(bar_full + rp.slot * 8, rp.phase);
      slot = rp.slot;
      rp.next();
    };
    auto release = [&](int slot) {
      if (lane == 0) mbar_arrive(bar_empty + slot * 8);
    };
    if (t_begin < t_end) {
      if (cw == 1) bar_arrive(1, 256);
      float s[64], o[64];
      uint32_t q[32], p[32];
      float m0, m1, l0 = 0.f, l1 = 0.f;
      auto ctx_ptr = [&](int t) {
        return g_ctx + (size_t)((t >> 4) * SEQ + (t & 15) * 128 + cw * 64 + warp * 16 + (lane >> 2)) * HD + (lane & 3) * 8;
      };
      int slot_q = 0, slot_v = 0, slot_k = 0;
      auto issue_pv = [&](bool accumulate) {
        const uint32_t dv = make_desc(base + slot_v * 32768, 16384);
#pragma unroll
        for (int kk = 0; kk < 8; kk++)
          wgmma_rs_n128<1>(o, p[4 * kk], p[4 * kk + 1], p[4 * kk + 2], p[4 * kk + 3], desc_add(dv, kk * 2048), kk != 0 || accumulate);
      };
      auto issue_qk = [&]() {
        const uint32_t dk = make_desc(base + slot_k * 32768, 16);
#pragma unroll
        for (int kk = 0; kk < 8; kk++)
          wgmma_rs_n128<0>(s, q[4 * kk], q[4 * kk + 1], q[4 * kk + 2], q[4 * kk + 3],
                           desc_add(dk, (kk >> 2) * 16384 + (kk & 3) * 32), kk != 0);
      };
      auto take_next = [&](bool last_block, bool more_tiles) {
        if (last_block && more_tiles) take(slot_q);
        take(slot_v);
        if (!last_block || more_tiles) take(slot_k);
      };

      auto start_tile = [&]() {
        const float a0 = __shfl_sync(0xffffffffu, s[0], lane & 28), a1 = __shfl_sync(0xffffffffu, s[2], lane & 28);
        m0 = fabsf(a0) <= SM_ZERO ? 0.f : a0;
        m1 = fabsf(a1) <= SM_ZERO ? 0.f : a1;
        l0 = 0.f;
        l1 = 0.f;
        mask_diag(s, cw, warp, lane);
      };

      int ti = t_begin;
      int j = sched.tile[ti] & 15;
      take(slot_q);
      load_q_frags(q, base + slot_q * 32768, cw, warp, lane);
      release(slot_q);
      take(slot_k);
      bar_sync(1 + cw, 256);
      wgmma_fence();
      issue_qk();
      wgmma_commit();
      bar_arrive(2 - cw, 256);
      int done_k = slot_k;
      bool more = ti + 1 < t_end;
      take_next(j == 0, more);
#pragma unroll
      for (int i = 0; i < 64; i++) o[i] = 0.f;
      wgmma_wait<0>();
      release(done_k);
      fence_regs(s);
      start_tile();
      bool fresh = true;
#pragma unroll 1
      while (true) {
        float r0, r1;
        bool general = !__all_sync(0xffffffffu, m0 == 0.f && m1 == 0.f), refresh = false;
        if (!general) {
          exp_pack<16, false>(s, p, m0, m1, r0, r1);
          general = refresh = __any_sync(0xffffffffu, !(r0 <= SM_LIMIT && r1 <= SM_LIMIT));
        }
        if (general) {
#pragma unroll 1
          while (true) {
            if (refresh) refresh_max(s, o, m0, m1, l0, l1);
            exp_pack<16, true>(s, p, m0, m1, r0, r1);
            if (refresh || !__any_sync(0xffffffffu, !(r0 <= SM_LIMIT && r1 <= SM_LIMIT))) break;
            refresh = true;
          }
        }
        l0 += r0;
        l1 += r1;
        if (j == 0) {
          if (!more) break;
          load_q_frags(q, base + slot_q * 32768, cw, warp, lane);
          release(slot_q);
        }
        bar_sync(1 + cw, 256);
        wgmma_fence();
        issue_pv(!fresh);
        issue_qk();
        wgmma_commit();
        bar_arrive(2 - cw, 256);
        const int done_v = slot_v;
        done_k = slot_k;
        fresh = j == 0;
        if (fresh) {
          j = sched.tile[++ti] & 15;
          more = ti + 1 < t_end;
        } else {
          j--;
        }
        take_next(j == 0, more);
        float i0, i1;
        if (fresh) row_recip(l0, l1, i0, i1);
        wgmma_wait<0>();
        release(done_v);
        release(done_k);
        fence_regs(s);
        fence_regs(o);
        if (fresh) {
          write_ctx(o, i0, i1, ctx_ptr(sched.tile[ti - 1]));
          start_tile();
        }
      }
      bar_sync(1 + cw, 256);
      wgmma_fence();
      issue_pv(!fresh);
      wgmma_commit();
      bar_arrive(2 - cw, 256);
      float i0, i1;
      row_recip(l0, l1, i0, i1);
      wgmma_wait<0>();
      fence_regs(o);
      write_ctx(o, i0, i1, ctx_ptr(sched.tile[t_end - 1]));
    }
  }
}
constexpr int TL_XBUF = 196608;
constexpr int TL_CS = TL_XBUF + 32768;
constexpr int TL_BARS = TL_CS + 1408;
constexpr int TL_SMEM = TL_BARS + 192 + 1024;
constexpr int ACT_PITCH = 1408;

__device__ __forceinline__ void tma_load_5d(uint32_t dst, const CUtensorMap* map, int c0, int c4, uint32_t bar) {
  asm volatile("cp.async.bulk.tensor.5d.shared::cluster.global.mbarrier::complete_tx::bytes [%0], [%1, {%3, %4, %4, %4, %5}], [%2];"
               ::"r"(dst), "l"(map), "r"(bar), "r"(c0), "r"(0), "r"(c4) : "memory");
}
__device__ __forceinline__ uint32_t relu_mul_bf16x2(uint32_t g, uint32_t u) {
  uint32_t r;
  asm("{\n.reg .b32 t;\nmax.NaN.bf16x2 t, %1, %3;\nmul.rn.bf16x2 %0, t, %2;\n}" : "=r"(r) : "r"(g), "r"(u), "r"(0u));
  return r;
}
__device__ __forceinline__ void team_arrive(unsigned int* ctr) {
  asm volatile("fence.acq_rel.gpu;\nred.relaxed.gpu.global.add.u32 [%0], 1;" ::"l"(ctr) : "memory");
}
__device__ __forceinline__ void st_global_v2(void* p, uint32_t a, uint32_t b) {
  asm volatile("st.global.v2.b32 [%0], {%1, %2};" ::"l"(p), "r"(a), "r"(b));
}

template <int NSTEPS>
__device__ __forceinline__ void gemm_split_k(float (&acc)[64], uint32_t base, uint32_t bar_full, int cw, int tid) {
  const uint32_t bar_empty = bar_full + 32;
#pragma unroll 1
  for (int s = 0; s < NSTEPS; s++) {
    const int st = s & 3;
    mbar_wait(bar_full + st * 8, (s >> 2) & 1);
    const uint32_t sa = base + st * 49152;
    const uint32_t da = make_desc(sa + cw * 8192, 16);
    const uint32_t db = make_desc(sa + 16384 + cw * 8192, 16384);
    wgmma_fence();
#pragma unroll
    for (int i = 0; i < 4; i++) wgmma_ss_n128<1>(acc, desc_add(da, i * 32), desc_add(db, i * 2048), (s | i) != 0);
    wgmma_commit();
    if (s > 0) {
      wgmma_wait<1>();
      if (tid == 0) mbar_arrive(bar_empty + ((s - 1) & 3) * 8);
    }
  }
  wgmma_wait<0>();
  if (tid == 0) mbar_arrive(bar_empty + ((NSTEPS - 1) & 3) * 8);
  fence_regs(acc);
}

template <int CW>
__device__ __forceinline__ void reduce_add_residual_t(const float (&acc)[64], const uint32_t (&res)[16], uint32_t (&pk)[16], uint32_t xbuf,
                                                      int tid) {
  constexpr int SEND = CW ? 0 : 32, KEEP = CW ? 32 : 0;
  const uint32_t wr = xbuf + CW * 16384 + tid * 16, rd = xbuf + (CW ^ 1) * 16384 + tid * 16;
#pragma unroll
  for (int i = 0; i < 8; i++)
    asm volatile("st.shared.v4.f32 [%0], {%1, %2, %3, %4};" ::"r"(wr + i * 2048), "f"(acc[SEND + 4 * i]), "f"(acc[SEND + 4 * i + 1]),
                 "f"(acc[SEND + 4 * i + 2]), "f"(acc[SEND + 4 * i + 3]) : "memory");
  bar_sync(1, 256);
#pragma unroll
  for (int i = 0; i < 8; i++) {
    float4 t;
    asm volatile("ld.shared.v4.f32 {%0, %1, %2, %3}, [%4];" : "=f"(t.x), "=f"(t.y), "=f"(t.z), "=f"(t.w) : "r"(rd + i * 2048) : "memory");
    const uint32_t p0 = pack_bf16(t.x + acc[KEEP + 4 * i], t.y + acc[KEEP + 4 * i + 1]);
    const uint32_t p1 = pack_bf16(t.z + acc[KEEP + 4 * i + 2], t.w + acc[KEEP + 4 * i + 3]);
    pk[2 * i] = pack_bf16(bf_lo(p0) + bf_lo(res[2 * i]), bf_hi(p0) + bf_hi(res[2 * i]));
    pk[2 * i + 1] = pack_bf16(bf_lo(p1) + bf_lo(res[2 * i + 1]), bf_hi(p1) + bf_hi(res[2 * i + 1]));
  }
}
__device__ __forceinline__ void reduce_add_residual(const float (&acc)[64], const uint32_t (&res)[16], uint32_t (&pk)[16], uint32_t xbuf,
                                                    int cw, int tid) {
  if (cw == 0) reduce_add_residual_t<0>(acc, res, pk, xbuf, tid);
  else reduce_add_residual_t<1>(acc, res, pk, xbuf, tid);
}

__global__ void __launch_bounds__(384, 1)
tail_kernel(const __grid_constant__ CUtensorMap mCtx, const __grid_constant__ CUtensorMap mWo, const __grid_constant__ CUtensorMap mH,
            const __grid_constant__ CUtensorMap mWg, const __grid_constant__ CUtensorMap mWu, const __grid_constant__ CUtensorMap mAct,
            const __grid_constant__ CUtensorMap mWd, const __grid_constant__ CUtensorMap mOut, const bf16* __restrict__ x) {
  extern __shared__ uint8_t smem_raw[];
  const uint32_t base = align1024(smem_u32(smem_raw));
  const uint32_t barC = base + TL_BARS, barD = barC + 64, barE = barD + 64;
  if (threadIdx.x == 0) {
    for (int i = 0; i < 12; i++) {
      mbar_init(barC + (i >> 2) * 64 + (i & 3) * 8, 1);
      mbar_init(barC + (i >> 2) * 64 + 32 + (i & 3) * 8, 2);
    }
    asm volatile("fence.mbarrier_init.release.cluster;" ::: "memory");
  }
  if (threadIdx.x == 32) {
    tma_prefetch_desc(&mWo);
    tma_prefetch_desc(&mCtx);
    tma_prefetch_desc(&mWg);
    tma_prefetch_desc(&mWu);
    tma_prefetch_desc(&mH);
    tma_prefetch_desc(&mWd);
    tma_prefetch_desc(&mAct);
    tma_prefetch_desc(&mOut);
  }
  __syncthreads();
  const int team = blockIdx.x >> 3, member = blockIdx.x & 7;
  const int mhalf = member >> 2, nt = member & 3;
  const int m64 = team * 2 + mhalf;
  const int n0 = member * 176;
  const int wg = threadIdx.x >> 7, warp = (threadIdx.x >> 5) & 3, lane = threadIdx.x & 31;
  if (wg == 0) {
    reg_dec<40>();
    if (warp == 0 && lane == 0) {
      auto load_wo = [&](int s) {
        const uint32_t dst = base + (s & 3) * 49152, fb = barC + (s & 3) * 8;
        mbar_expect_tx(fb, 49152);
        tma_load_2d(dst + 16384, &mWo, nt * 128, s * 128, fb);
        tma_load_2d(dst + 32768, &mWo, nt * 128 + 64, s * 128, fb);
      };
      for (int s = 0; s < 4; s++) load_wo(s);
      pdl_wait();
      for (int s = 0; s < NH; s++) {
        const uint32_t dst = base + (s & 3) * 49152, fb = barC + (s & 3) * 8;
        if (s >= 4) {
          mbar_wait(barC + 32 + (s & 3) * 8, ((s >> 2) & 1) ^ 1);
          load_wo(s);
        }
        tma_load_2d(dst, &mCtx, 0, s * SEQ + m64 * 64, fb);
        tma_load_2d(dst + 8192, &mCtx, 64, s * SEQ + m64 * 64, fb);
      }
      for (int it = 0; it < 8; it++) {
        const int st = it % 3;
        if (it < 3) {
          if (it == 0) mbar_wait(barC + 32, 1);
          mbar_wait(barC + 32 + (it + 1) * 8, 1);
        } else {
          mbar_wait(barD + 32 + st * 8, ((it / 3) & 1) ^ 1);
        }
        const uint32_t dst = base + st * 65536, fb = barD + st * 8;
        mbar_expect_tx(fb, 65536);
#pragma unroll
        for (int c = 0; c < 3; c++) {
          tma_load_5d(dst + 16384 + c * 8192, &mWg, n0 + c * 64, it * 2, fb);
          tma_load_5d(dst + 40960 + c * 8192, &mWu, n0 + c * 64, it * 2, fb);
        }
        if (it == 2) {
          spin_until(g_team + team * 4, 16);
          asm volatile("fence.proxy.async.global;" ::: "memory");
          tma_load_2d(base, &mH, 0, team * 128, barD);
          tma_load_2d(base + 65536, &mH, 64, team * 128, barD + 8);
        }
        if (it >= 2) tma_load_2d(dst, &mH, it * 64, team * 128, fb);
      }
      for (int s = 0; s < 11; s++) {
        const int st = s & 3;
        if (s < 4) {
          if (s == 0) mbar_wait(barD + 32, 0);
          if (s == 1) mbar_wait(barD + 32 + 8, 0);
          if (s == 2) mbar_wait(barD + 32 + 16, 1);
        } else {
          mbar_wait(barE + 32 + st * 8, ((s >> 2) & 1) ^ 1);
        }
        const uint32_t dst = base + st * 49152, fb = barE + st * 8;
        mbar_expect_tx(fb, 49152);
        tma_load_5d(dst + 16384, &mWd, nt * 128, s * 8, fb);
        tma_load_5d(dst + 32768, &mWd, nt * 128 + 64, s * 8, fb);
        if (s == 3) {
          spin_until(g_team + team * 4 + 1, 16);
          asm volatile("fence.proxy.async.global;" ::: "memory");
          for (int i = 0; i < 3; i++) {
            tma_load_2d(base + i * 49152, &mAct, i * 128, m64 * 64, barE + i * 8);
            tma_load_2d(base + i * 49152 + 8192, &mAct, i * 128 + 64, m64 * 64, barE + i * 8);
          }
        }
        if (s >= 3) {
          tma_load_2d(dst, &mAct, s * 128, m64 * 64, fb);
          tma_load_2d(dst + 8192, &mAct, s * 128 + 64, m64 * 64, fb);
        }
      }
    } else if (warp == 1) {
      pdl_wait();
      if (blockIdx.x == 0 && lane < 16) g_ln_count[lane] = 0;
      for (int i = lane; i < 352; i += 32) {
        const float c = __ldcg(g_cs + (i / 176) * 1408 + n0 + (i % 176));
        asm volatile("st.shared.f32 [%0], %1;" ::"r"(base + TL_CS + i * 4), "f"(c) : "memory");
      }
      bar_arrive(4, 288);
    }
  } else {
    reg_inc<232>();
    const int cw = wg - 1;
    const int tid = threadIdx.x & 127;
    const uint32_t xbuf = base + TL_XBUF;
    uint32_t hk[16];
    const int row0 = m64 * 64 + warp * 16 + (lane >> 2);
    {
      const int col0 = nt * 128 + cw * 64 + (lane & 3) * 2;
      uint32_t res[16];
#pragma unroll
      for (int i = 0; i < 8; i++) {
        res[2 * i] = __ldg(reinterpret_cast<const uint32_t*>(x + (size_t)row0 * DM + col0 + 8 * i));
        res[2 * i + 1] = __ldg(reinterpret_cast<const uint32_t*>(x + (size_t)(row0 + 8) * DM + col0 + 8 * i));
      }
      float acc[64];
      gemm_split_k<NH>(acc, base, barC, cw, tid);
      reduce_add_residual(acc, res, hk, xbuf, cw, tid);
      bf16* const hp = g_h + (size_t)row0 * DM + nt * 128 + cw * 64 + (lane & 3) * 8;
#pragma unroll
      for (int a = 0; a < 2; a++) {
        st_global_v4(hp + 32 * a, hk[8 * a], hk[8 * a + 2], hk[8 * a + 4], hk[8 * a + 6]);
        st_global_v4(hp + 32 * a + 8 * DM, hk[8 * a + 1], hk[8 * a + 3], hk[8 * a + 5], hk[8 * a + 7]);
      }
      bar_sync(2 + cw, 128);
      if (tid == 0) team_arrive(g_team + team * 4);
      float s0 = 0.f, s1 = 0.f;
#pragma unroll
      for (int i = 0; i < 8; i++) {
        s0 += bf_lo(hk[2 * i]) + bf_hi(hk[2 * i]);
        s1 += bf_lo(hk[2 * i + 1]) + bf_hi(hk[2 * i + 1]);
      }
      s0 += __shfl_xor_sync(0xffffffffu, s0, 1); s1 += __shfl_xor_sync(0xffffffffu, s1, 1);
      s0 += __shfl_xor_sync(0xffffffffu, s0, 2); s1 += __shfl_xor_sync(0xffffffffu, s1, 2);
      const float mu0 = s0 * (1.f / 64), mu1 = s1 * (1.f / 64);
      float q0 = 0.f, q1 = 0.f;
#pragma unroll
      for (int i = 0; i < 8; i++) {
        const float a = bf_lo(hk[2 * i]) - mu0, b = bf_hi(hk[2 * i]) - mu0, c = bf_lo(hk[2 * i + 1]) - mu1, d = bf_hi(hk[2 * i + 1]) - mu1;
        q0 += a * a + b * b;
        q1 += c * c + d * d;
      }
      q0 += __shfl_xor_sync(0xffffffffu, q0, 1); q1 += __shfl_xor_sync(0xffffffffu, q1, 1);
      q0 += __shfl_xor_sync(0xffffffffu, q0, 2); q1 += __shfl_xor_sync(0xffffffffu, q1, 2);
      if ((lane & 3) == 0) {
        g_stats[row0 * 8 + nt * 2 + cw] = make_float2(mu0, q0);
        g_stats[(row0 + 8) * 8 + nt * 2 + cw] = make_float2(mu1, q1);
      }
      bar_sync(2 + cw, 128);
      if (tid == 0) team_arrive(g_team + team * 4 + 2);
    }
    {
      float ag[88], au[88];
      float mean[2], rstd[2];
      int st = 0, prev = 0;
      uint32_t ph = 0;
#pragma unroll 1
      for (int it = 0; it < 8; it++) {
        mbar_wait(barD + st * 8, ph);
        const uint32_t sa = base + st * 65536;
        const uint32_t da = make_desc(sa + cw * 8192, 16);
        const uint32_t dg = make_desc(sa + 16384, 8192);
        const uint32_t du = make_desc(sa + 40960, 8192);
        wgmma_fence();
#pragma unroll
        for (int kk = 0; kk < 4; kk++) {
          wgmma_ss_n176<1>(ag, desc_add(da, kk * 32), desc_add(dg, kk * 2048), (it | kk) != 0);
          wgmma_ss_n176<1>(au, desc_add(da, kk * 32), desc_add(du, kk * 2048), (it | kk) != 0);
        }
        wgmma_commit();
        if (it > 0) {
          wgmma_wait<1>();
          if (tid == 0) mbar_arrive(barD + 32 + prev * 8);
        }
        prev = st;
        if (++st == 3) { st = 0; ph ^= 1; }
      }
      if (tid == 0) spin_until(g_team + team * 4 + 2, 16);
      bar_sync(2 + cw, 128);
      const int drow = team * 128 + cw * 64 + warp * 16 + (lane >> 2);
#pragma unroll
      for (int r = 0; r < 2; r++) {
        const float4* sp = reinterpret_cast<const float4*>(g_stats + (drow + 8 * r) * 8);
        const float4 a = __ldcg(sp), b = __ldcg(sp + 1), c = __ldcg(sp + 2), d = __ldcg(sp + 3);
        const float mu = (a.x + a.z + b.x + b.z + c.x + c.z + d.x + d.z) * 0.125f;
        float m2 = a.y + a.w + b.y + b.w + c.y + c.w + d.y + d.w;
        m2 += 64.f * ((a.x - mu) * (a.x - mu) + (a.z - mu) * (a.z - mu) + (b.x - mu) * (b.x - mu) + (b.z - mu) * (b.z - mu) +
                      (c.x - mu) * (c.x - mu) + (c.z - mu) * (c.z - mu) + (d.x - mu) * (d.x - mu) + (d.z - mu) * (d.z - mu));
        mean[r] = mu;
        rstd[r] = 1.f / sqrtf(m2 * (1.f / DM) + 1e-5f);
      }
      bar_sync(4, 288);
      wgmma_wait<0>();
      if (tid == 0) mbar_arrive(barD + 32 + prev * 8);
      fence_regs(ag);
      fence_regs(au);
      bf16* const actp = g_act + (size_t)drow * ACT_PITCH + n0 + (lane & 3) * 4;
      uint32_t csb = base + TL_CS + (lane & 3) * 8;
      asm volatile("" : "+r"(csb)::"memory");
#pragma unroll
      for (int j = 0; j < 11; j++) {
        uint32_t o4[4];
#pragma unroll
        for (int hh = 0; hh < 2; hh++) {
          const int i = 2 * j + hh;
          float2 cg, cu;
          asm("ld.shared.v2.f32 {%0, %1}, [%2];" : "=f"(cg.x), "=f"(cg.y) : "r"(csb + i * 32));
          asm("ld.shared.v2.f32 {%0, %1}, [%2];" : "=f"(cu.x), "=f"(cu.y) : "r"(csb + 704 + i * 32));
#pragma unroll
          for (int r = 0; r < 2; r++) {
            const uint32_t g = pack_bf16(fmaf(-mean[r], cg.x, ag[4 * i + 2 * r]) * rstd[r], fmaf(-mean[r], cg.y, ag[4 * i + 2 * r + 1]) * rstd[r]);
            const uint32_t u = pack_bf16(fmaf(-mean[r], cu.x, au[4 * i + 2 * r]) * rstd[r], fmaf(-mean[r], cu.y, au[4 * i + 2 * r + 1]) * rstd[r]);
            o4[2 * hh + r] = relu_mul_bf16x2(g, u);
          }
        }
        st_global_v2(actp + j * 16, o4[0], o4[2]);
        st_global_v2(actp + j * 16 + 8 * ACT_PITCH, o4[1], o4[3]);
      }
      bar_sync(2 + cw, 128);
      if (tid == 0) team_arrive(g_team + team * 4 + 1);
    }
    {
      float acc[64];
      gemm_split_k<11>(acc, base, barE, cw, tid);
      uint32_t pk[16];
      reduce_add_residual(acc, hk, pk, xbuf, cw, tid);
      const uint32_t mystag = xbuf + (cw ^ 1) * 16384;
      bar_sync(2 + cw, 128);
      const int row = warp * 16 + (lane & 7) + ((lane >> 3) & 1) * 8;
#pragma unroll
      for (int j = 0; j < 4; j++) {
        const int chunk = 2 * j + (lane >> 4);
        stmatrix_x4(mystag + row * 128 + ((chunk ^ (row & 7)) << 4), pk[4 * j], pk[4 * j + 1], pk[4 * j + 2], pk[4 * j + 3]);
      }
      fence_async_smem();
      bar_sync(2 + cw, 128);
      if (tid == 0) {
        tma_store_2d(&mOut, mystag, nt * 128 + cw * 64, m64 * 64);
        bulk_commit();
        bulk_wait_read<0>();
      }
    }
  }
}
typedef CUresult (*EncodeTiledFn)(CUtensorMap*, CUtensorMapDataType, cuuint32_t, void*, const cuuint64_t*, const cuuint64_t*,
                                  const cuuint32_t*, const cuuint32_t*, CUtensorMapInterleave, CUtensorMapSwizzle,
                                  CUtensorMapL2promotion, CUtensorMapFloatOOBfill);

EncodeTiledFn encode_fn() {
  static EncodeTiledFn fn = nullptr;
  if (!fn) {
    void* p = nullptr;
    cudaDriverEntryPointQueryResult q;
    cudaGetDriverEntryPoint("cuTensorMapEncodeTiled", &p, cudaEnableDefault, &q);
    fn = (EncodeTiledFn)p;
  }
  return fn;
}

CUtensorMap map2d(const void* ptr, uint64_t inner, uint64_t outer, uint64_t pitch_elems, uint32_t box_inner, uint32_t box_outer,
                  CUtensorMapSwizzle sw = CU_TENSOR_MAP_SWIZZLE_128B) {
  CUtensorMap m;
  cuuint64_t dims[2] = {inner, outer};
  cuuint64_t strides[1] = {pitch_elems * 2};
  cuuint32_t box[2] = {box_inner, box_outer};
  cuuint32_t es[2] = {1, 1};
  encode_fn()(&m, CU_TENSOR_MAP_DATA_TYPE_BFLOAT16, 2, const_cast<void*>(ptr), dims, strides, box, es, CU_TENSOR_MAP_INTERLEAVE_NONE, sw,
              CU_TENSOR_MAP_L2_PROMOTION_L2_256B, CU_TENSOR_MAP_FLOAT_OOB_FILL_NONE);
  return m;
}

CUtensorMap map3d_chunks(const void* ptr, uint64_t rows, uint64_t cols, uint32_t box_rows, uint32_t chunks) {
  CUtensorMap m;
  cuuint64_t dims[3] = {64, rows, cols / 64};
  cuuint64_t strides[2] = {cols * 2, 128};
  cuuint32_t box[3] = {64, box_rows, chunks};
  cuuint32_t es[3] = {1, 1, 1};
  encode_fn()(&m, CU_TENSOR_MAP_DATA_TYPE_BFLOAT16, 3, const_cast<void*>(ptr), dims, strides, box, es, CU_TENSOR_MAP_INTERLEAVE_NONE,
              CU_TENSOR_MAP_SWIZZLE_128B, CU_TENSOR_MAP_L2_PROMOTION_L2_256B, CU_TENSOR_MAP_FLOAT_OOB_FILL_NONE);
  return m;
}

CUtensorMap map5d_perm32(const void* ptr, uint64_t rows, uint64_t cols, uint32_t groups) {
  CUtensorMap m;
  const cuuint64_t row = cols * 2;
  cuuint64_t dims[5] = {cols, 2, 4, 4, rows / 32};
  cuuint64_t strides[4] = {row, 8 * row, 2 * row, 32 * row};
  cuuint32_t box[5] = {64, 2, 4, 4, groups};
  cuuint32_t es[5] = {1, 1, 1, 1, 1};
  encode_fn()(&m, CU_TENSOR_MAP_DATA_TYPE_BFLOAT16, 5, const_cast<void*>(ptr), dims, strides, box, es, CU_TENSOR_MAP_INTERLEAVE_NONE,
              CU_TENSOR_MAP_SWIZZLE_128B, CU_TENSOR_MAP_L2_PROMOTION_L2_256B, CU_TENSOR_MAP_FLOAT_OOB_FILL_NONE);
  return m;
}
CUtensorMap map5d_perm16(const void* ptr, uint64_t rows, uint64_t cols, uint32_t groups) {
  CUtensorMap m;
  const cuuint64_t row = cols * 2;
  cuuint64_t dims[5] = {cols, 2, 2, 4, rows / 16};
  cuuint64_t strides[4] = {row, 8 * row, 2 * row, 16 * row};
  cuuint32_t box[5] = {64, 2, 2, 4, groups};
  cuuint32_t es[5] = {1, 1, 1, 1, 1};
  encode_fn()(&m, CU_TENSOR_MAP_DATA_TYPE_BFLOAT16, 5, const_cast<void*>(ptr), dims, strides, box, es, CU_TENSOR_MAP_INTERLEAVE_NONE,
              CU_TENSOR_MAP_SWIZZLE_128B, CU_TENSOR_MAP_L2_PROMOTION_L2_256B, CU_TENSOR_MAP_FLOAT_OOB_FILL_NONE);
  return m;
}

template <typename T> void* sym_addr(T& sym) {
  void* p = nullptr;
  cudaGetSymbolAddress(&p, sym);
  return p;
}

void build_schedule(AttnSched& s, int ncta) {
  static int lists[134][64];
  int cnt[134] = {0};
  float load[134] = {0};
  auto cost = [](int tile) { return (float)((tile & 15) + 1) + 0.65f; };
    constexpr int GROUP = 32;
  for (int g = 0; g < NH / GROUP; g++)
    for (int qb = 15; qb >= 0; qb--)
      for (int h = g * GROUP; h < (g + 1) * GROUP; h++) {
        int best = 0;
        for (int c = 1; c < ncta; c++)
          if (load[c] < load[best]) best = c;
        lists[best][cnt[best]++] = h * 16 + qb;
        load[best] += cost(h * 16 + qb);
      }
  for (int iter = 0; iter < 4000; iter++) {
    int hi = 0;
    for (int c = 1; c < ncta; c++)
      if (load[c] > load[hi]) hi = c;
    float best_max = load[hi] - 1e-3f;
    int bi = -1, bc = -1, bj = -1;
    for (int c = 0; c < ncta; c++) {
      if (c == hi) continue;
      for (int i = 0; i < cnt[hi]; i++) {
        const float ci = cost(lists[hi][i]);
        for (int j = 0; j < cnt[c]; j++) {
          if (lists[c][j] / (16 * GROUP) != lists[hi][i] / (16 * GROUP)) continue;
          const float cj = cost(lists[c][j]);
          const float m = fmaxf(load[hi] - ci + cj, load[c] - cj + ci);
          if (m < best_max) { best_max = m; bi = i; bc = c; bj = j; }
        }
      }
    }
    if (bi < 0) break;
    const int ti = lists[hi][bi], tj = lists[bc][bj];
    lists[hi][bi] = tj;
    lists[bc][bj] = ti;
    load[hi] += cost(tj) - cost(ti);
    load[bc] += cost(ti) - cost(tj);
  }
  int pos = 0;
  for (int c = 0; c < ncta; c++) {
    s.start[c] = pos;
    for (int i = 0; i < cnt[c]; i++) s.tile[pos++] = lists[c][i];
  }
  for (int c = ncta; c < 134; c++) s.start[c] = pos;
}

template <typename... KArgs, typename... Args>
void launch(void (*kern)(KArgs...), int grid, int smem, bool pdl, Args... args) {
  cudaLaunchConfig_t cfg = {};
  cfg.gridDim = dim3(grid);
  cfg.blockDim = dim3(384);
  cfg.dynamicSmemBytes = smem;
  cfg.stream = cudaStreamPerThread;
  cudaLaunchAttribute at[1];
  at[0].id = cudaLaunchAttributeProgrammaticStreamSerialization;
  at[0].val.programmaticStreamSerializationAllowed = 1;
  cfg.attrs = at;
  cfg.numAttrs = pdl ? 1 : 0;
  cudaLaunchKernelEx(&cfg, kern, KArgs(args)...);
}

}

extern "C" void kernel_launch(void* const* d_in, const int* in_sizes, int n_in, void* d_out, int out_size) {
  const bf16* x = (const bf16*)d_in[0];
  const bf16* ckv = (const bf16*)d_in[1];
  const bf16* wq = (const bf16*)d_in[2];
  const bf16* wuk = (const bf16*)d_in[3];
  const bf16* wuv = (const bf16*)d_in[4];
  const bf16* wo = (const bf16*)d_in[5];
  const bf16* wgate = (const bf16*)d_in[7];
  const bf16* wup = (const bf16*)d_in[8];
  const bf16* wdown = (const bf16*)d_in[9];
  bf16* out = (bf16*)d_out;

  static bool init = false;
  static AttnSched sched;
  static int nsm = 132;
  static void *p_xn, *p_q, *p_k, *p_v, *p_ctx, *p_h, *p_act;
  if (!init) {
    cudaFuncSetAttribute(qkv_kernel, cudaFuncAttributeMaxDynamicSharedMemorySize, KV_SMEM);
    cudaFuncSetAttribute(attn_kernel, cudaFuncAttributeMaxDynamicSharedMemorySize, AT_SMEM);
    cudaFuncSetAttribute(tail_kernel, cudaFuncAttributeMaxDynamicSharedMemorySize, TL_SMEM);
    int dev = 0;
    cudaGetDevice(&dev);
    cudaDeviceGetAttribute(&nsm, cudaDevAttrMultiProcessorCount, dev);
    if (nsm > 132) nsm = 132;
    build_schedule(sched, nsm);
    p_xn = sym_addr(g_xn); p_q = sym_addr(g_q); p_k = sym_addr(g_k); p_v = sym_addr(g_v); p_ctx = sym_addr(g_ctx); p_h = sym_addr(g_h); p_act = sym_addr(g_act);
    init = true;
  }

  const CUtensorMap mCkv = map2d(ckv, DM, SEQ, DM, 64, 128);
  const CUtensorMap mXn = map2d(p_xn, DM, SEQ, DM, 64, 128);
  const CUtensorMap mWk = map3d_chunks(wuk, DM, NH * HD, 64, 4);
  const CUtensorMap mWv = map3d_chunks(wuv, DM, NH * HD, 64, 4);
  const CUtensorMap mWq = map3d_chunks(wq, DM, NH * HD, 64, 4);
  launch(qkv_kernel, 128, KV_SMEM, false, mCkv, mXn, mWk, mWv, mWq, x, wgate, wup);

  const CUtensorMap mQ = map2d(p_q, HD, NH * SEQ, HD, 64, 128);
  const CUtensorMap mK = map2d(p_k, HD, NH * SEQ, HD, 64, 128);
  const CUtensorMap mV = map2d(p_v, HD, NH * SEQ, HD, 64, 128);
  launch(attn_kernel, nsm, AT_SMEM, true, mQ, mK, mV, sched);

  const CUtensorMap mCtx = map2d(p_ctx, HD, NH * SEQ, HD, 64, 64);
  const CUtensorMap mWo = map2d(wo, DM, NH * HD, DM, 64, 128);
  const CUtensorMap mH = map2d(p_h, DM, SEQ, DM, 64, 128);
  const CUtensorMap mWg = map5d_perm32(wgate, DM, FF, 2);
  const CUtensorMap mWu = map5d_perm32(wup, DM, FF, 2);
  const CUtensorMap mAct = map2d(p_act, ACT_PITCH, SEQ, ACT_PITCH, 64, 64);
  const CUtensorMap mWd = map5d_perm16(wdown, FF, DM, 8);
  const CUtensorMap mOut = map2d(out, DM, SEQ, DM, 64, 64);
  launch(tail_kernel, 128, TL_SMEM, true, mCtx, mWo, mH, mWg, mWu, mAct, mWd, mOut, x);
}
```

```cpp
#include <cuda_runtime.h>
#include <cuda_bf16.h>
#include <cuda.h>
#include <stdint.h>

#pragma nv_diag_suppress 549

namespace {

constexpr int SEQ = 2048, DM = 512, NH = 32, HD = 128, FF = 1376;
typedef __nv_bfloat16 bf16;

__device__ __align__(1024) bf16 g_xn[SEQ * DM];
__device__ __align__(1024) bf16 g_q[NH * SEQ * HD];
__device__ __align__(1024) bf16 g_k[NH * SEQ * HD];
__device__ __align__(1024) bf16 g_v[NH * SEQ * HD];
__device__ __align__(1024) bf16 g_ctx[NH * SEQ * HD];
__device__ __align__(1024) bf16 g_h[SEQ * DM];
__device__ __align__(1024) bf16 g_act[SEQ * 1408];
__device__ __align__(1024) float2 g_stats[SEQ * 8];
__device__ __align__(1024) float g_cs[2 * 1408];

__device__ unsigned int g_team[64];
__device__ unsigned int g_ln_count[16];

__device__ __forceinline__ uint32_t smem_u32(const void* p) { return (uint32_t)__cvta_generic_to_shared(p); }
__device__ __forceinline__ void mbar_init(uint32_t bar, uint32_t cnt) {
  asm volatile("mbarrier.init.shared::cta.b64 [%0], %1;" ::"r"(bar), "r"(cnt));
}
__device__ __forceinline__ void mbar_expect_tx(uint32_t bar, uint32_t bytes) {
  asm volatile("mbarrier.arrive.expect_tx.shared::cta.b64 _, [%0], %1;" ::"r"(bar), "r"(bytes) : "memory");
}
__device__ __forceinline__ void mbar_arrive(uint32_t bar) {
  asm volatile("mbarrier.arrive.shared::cta.b64 _, [%0];" ::"r"(bar) : "memory");
}
__device__ __forceinline__ void mbar_wait(uint32_t bar, uint32_t parity) {
  asm volatile(
      "{\n.reg .pred p;\n.reg .u32 c;\n"
      "mov.u32 c, 0;\n"
      "WAIT_LOOP:\n"
      "mbarrier.try_wait.parity.shared::cta.b64 p, [%0], %1;\n"
      "@p bra WAIT_DONE;\n"
      "add.u32 c, c, 1;\n"
      "setp.lt.u32 p, c, 0x400000;\n"
      "@p bra WAIT_LOOP;\n"
      "trap;\n"
      "WAIT_DONE:\n}"
      ::"r"(bar), "r"(parity) : "memory");
}
__device__ __forceinline__ void spin_until(const unsigned int* ctr, unsigned int target) {
  asm volatile(
      "{\n.reg .pred p;\n.reg .u32 c, v;\n"
      "mov.u32 c, 0;\n"
      "SPIN_LOOP:\n"
      "ld.acquire.gpu.global.u32 v, [%0];\n"
      "setp.ge.u32 p, v, %1;\n"
      "@p bra SPIN_DONE;\n"
      "add.u32 c, c, 1;\n"
      "setp.lt.u32 p, c, 0x1000000;\n"
      "@p bra SPIN_LOOP;\n"
      "trap;\n"
      "SPIN_DONE:\n}"
      ::"l"(ctr), "r"(target) : "memory");
}
__device__ __forceinline__ void tma_load_2d(uint32_t dst, const CUtensorMap* map, int c0, int c1, uint32_t bar) {
  asm volatile("cp.async.bulk.tensor.2d.shared::cluster.global.mbarrier::complete_tx::bytes [%0], [%1, {%3, %4}], [%2];"
               ::"r"(dst), "l"(map), "r"(bar), "r"(c0), "r"(c1) : "memory");
}
__device__ __forceinline__ void tma_load_3d(uint32_t dst, const CUtensorMap* map, int c0, int c1, int c2, uint32_t bar) {
  asm volatile("cp.async.bulk.tensor.3d.shared::cluster.global.mbarrier::complete_tx::bytes [%0], [%1, {%3, %4, %5}], [%2];"
               ::"r"(dst), "l"(map), "r"(bar), "r"(c0), "r"(c1), "r"(c2) : "memory");
}
__device__ __forceinline__ void tma_store_2d(const CUtensorMap* map, uint32_t src, int c0, int c1) {
  asm volatile("cp.async.bulk.tensor.2d.global.shared::cta.bulk_group [%0, {%2, %3}], [%1];"
               ::"l"(map), "r"(src), "r"(c0), "r"(c1) : "memory");
}
__device__ __forceinline__ void tma_prefetch_desc(const CUtensorMap* map) {
  asm volatile("prefetch.tensormap [%0];" ::"l"(map) : "memory");
}
__device__ __forceinline__ void bulk_commit() { asm volatile("cp.async.bulk.commit_group;" ::: "memory"); }
template <int N> __device__ __forceinline__ void bulk_wait_read() { asm volatile("cp.async.bulk.wait_group.read %0;" ::"n"(N) : "memory"); }
template <int N> __device__ __forceinline__ void bulk_wait() { asm volatile("cp.async.bulk.wait_group %0;" ::"n"(N) : "memory"); }
__device__ __forceinline__ void fence_async_smem() { asm volatile("fence.proxy.async.shared::cta;" ::: "memory"); }
__device__ __forceinline__ void bar_sync(int id, int n) { asm volatile("bar.sync %0, %1;" ::"r"(id), "r"(n) : "memory"); }
__device__ __forceinline__ void bar_arrive(int id, int n) { asm volatile("bar.arrive %0, %1;" ::"r"(id), "r"(n) : "memory"); }
__device__ __forceinline__ void pdl_wait() { asm volatile("griddepcontrol.wait;" ::: "memory"); }
__device__ __forceinline__ void pdl_launch() { asm volatile("griddepcontrol.launch_dependents;" ::: "memory"); }
template <int N> __device__ __forceinline__ void reg_inc() { asm volatile("setmaxnreg.inc.sync.aligned.u32 %0;" ::"n"(N)); }
template <int N> __device__ __forceinline__ void reg_dec() { asm volatile("setmaxnreg.dec.sync.aligned.u32 %0;" ::"n"(N)); }
__device__ __forceinline__ void wgmma_fence() { asm volatile("wgmma.fence.sync.aligned;" ::: "memory"); }
__device__ __forceinline__ void wgmma_commit() { asm volatile("wgmma.commit_group.sync.aligned;" ::: "memory"); }
template <int N> __device__ __forceinline__ void wgmma_wait() { asm volatile("wgmma.wait_group.sync.aligned %0;" ::"n"(N) : "memory"); }
template <int N> __device__ __forceinline__ void fence_regs(float (&r)[N]) {
#pragma unroll
  for (int i = 0; i < N; i++) asm volatile("" : "+f"(r[i])::"memory");
}
template <int N> __device__ __forceinline__ void fence_regs(uint32_t (&r)[N]) {
#pragma unroll
  for (int i = 0; i < N; i++) asm volatile("" : "+r"(r[i])::"memory");
}
__device__ __forceinline__ uint32_t make_desc(uint32_t addr, uint32_t lbo_bytes) { return ((addr & 0x3FFFF) >> 4) | ((lbo_bytes >> 4) << 16); }
__device__ __forceinline__ uint32_t desc_add(uint32_t d, uint32_t bytes) { return d + (bytes >> 4); }
__device__ __forceinline__ uint32_t pack_bf16(float lo, float hi) {
  uint32_t r;
  asm("cvt.rn.bf16x2.f32 %0, %1, %2;" : "=r"(r) : "f"(hi), "f"(lo));
  return r;
}
__device__ __forceinline__ float bf_lo(uint32_t v) { return __uint_as_float(v << 16); }
__device__ __forceinline__ float bf_hi(uint32_t v) { return __uint_as_float(v & 0xffff0000u); }
__device__ __forceinline__ float ex2(float x) {
  float y;
  asm("ex2.approx.ftz.f32 %0, %1;" : "=f"(y) : "f"(x));
  return y;
}
__device__ __forceinline__ void stmatrix_x4(uint32_t addr, uint32_t a, uint32_t b, uint32_t c, uint32_t d) {
  asm volatile("stmatrix.sync.aligned.m8n8.x4.shared.b16 [%0], {%1, %2, %3, %4};"
               ::"r"(addr), "r"(a), "r"(b), "r"(c), "r"(d) : "memory");
}
__device__ __forceinline__ uint32_t align1024(uint32_t a) { return (a + 1023u) & ~1023u; }

template <int TB>
__device__ __forceinline__ void wgmma_ss_n128(float (&d)[64], uint32_t da, uint32_t db, int scale_d) {
  asm volatile("{\n.reg .pred p;\n.reg .b64 da, db;\nsetp.ne.b32 p, %66, 0;\nmov.b64 da, {%64, 0x40000040};\nmov.b64 db, {%65, 0x40000040};\n"
    "wgmma.mma_async.sync.aligned.m64n128k16.f32.bf16.bf16 "
    "{%0, %1, %2, %3, %4, %5, %6, %7, %8, %9, %10, %11, %12, %13, %14, %15, "
    "%16, %17, %18, %19, %20, %21, %22, %23, %24, %25, %26, %27, %28, %29, %30, %31, "
    "%32, %33, %34, %35, %36, %37, %38, %39, %40, %41, %42, %43, %44, %45, %46, %47, "
    "%48, %49, %50, %51, %52, %53, %54, %55, %56, %57, %58, %59, %60, %61, %62, %63}, "
    "da, db, p, 1, 1, 0, %67;\n}\n"
    :
      "+f"(d[0]), "+f"(d[1]), "+f"(d[2]), "+f"(d[3]), "+f"(d[4]), "+f"(d[5]), "+f"(d[6]), "+f"(d[7]),
      "+f"(d[8]), "+f"(d[9]), "+f"(d[10]), "+f"(d[11]), "+f"(d[12]), "+f"(d[13]), "+f"(d[14]), "+f"(d[15]),
      "+f"(d[16]), "+f"(d[17]), "+f"(d[18]), "+f"(d[19]), "+f"(d[20]), "+f"(d[21]), "+f"(d[22]), "+f"(d[23]),
      "+f"(d[24]), "+f"(d[25]), "+f"(d[26]), "+f"(d[27]), "+f"(d[28]), "+f"(d[29]), "+f"(d[30]), "+f"(d[31]),
      "+f"(d[32]), "+f"(d[33]), "+f"(d[34]), "+f"(d[35]), "+f"(d[36]), "+f"(d[37]), "+f"(d[38]), "+f"(d[39]),
      "+f"(d[40]), "+f"(d[41]), "+f"(d[42]), "+f"(d[43]), "+f"(d[44]), "+f"(d[45]), "+f"(d[46]), "+f"(d[47]),
      "+f"(d[48]), "+f"(d[49]), "+f"(d[50]), "+f"(d[51]), "+f"(d[52]), "+f"(d[53]), "+f"(d[54]), "+f"(d[55]),
      "+f"(d[56]), "+f"(d[57]), "+f"(d[58]), "+f"(d[59]), "+f"(d[60]), "+f"(d[61]), "+f"(d[62]), "+f"(d[63])
    : "r"(da), "r"(db), "r"(scale_d), "n"(TB));
}
template <int TB>
__device__ __forceinline__ void wgmma_rs_n128(float (&d)[64], uint32_t a0, uint32_t a1, uint32_t a2, uint32_t a3, uint32_t db, int scale_d) {
  asm volatile("{\n.reg .pred p;\n.reg .b64 db;\nsetp.ne.b32 p, %69, 0;\nmov.b64 db, {%68, 0x40000040};\n"
    "wgmma.mma_async.sync.aligned.m64n128k16.f32.bf16.bf16 "
    "{%0, %1, %2, %3, %4, %5, %6, %7, %8, %9, %10, %11, %12, %13, %14, %15, "
    "%16, %17, %18, %19, %20, %21, %22, %23, %24, %25, %26, %27, %28, %29, %30, %31, "
    "%32, %33, %34, %35, %36, %37, %38, %39, %40, %41, %42, %43, %44, %45, %46, %47, "
    "%48, %49, %50, %51, %52, %53, %54, %55, %56, %57, %58, %59, %60, %61, %62, %63}, "
    "{%64, %65, %66, %67}, db, p, 1, 1, %70;\n}\n"
    :
      "+f"(d[0]), "+f"(d[1]), "+f"(d[2]), "+f"(d[3]), "+f"(d[4]), "+f"(d[5]), "+f"(d[6]), "+f"(d[7]),
      "+f"(d[8]), "+f"(d[9]), "+f"(d[10]), "+f"(d[11]), "+f"(d[12]), "+f"(d[13]), "+f"(d[14]), "+f"(d[15]),
      "+f"(d[16]), "+f"(d[17]), "+f"(d[18]), "+f"(d[19]), "+f"(d[20]), "+f"(d[21]), "+f"(d[22]), "+f"(d[23]),
      "+f"(d[24]), "+f"(d[25]), "+f"(d[26]), "+f"(d[27]), "+f"(d[28]), "+f"(d[29]), "+f"(d[30]), "+f"(d[31]),
      "+f"(d[32]), "+f"(d[33]), "+f"(d[34]), "+f"(d[35]), "+f"(d[36]), "+f"(d[37]), "+f"(d[38]), "+f"(d[39]),
      "+f"(d[40]), "+f"(d[41]), "+f"(d[42]), "+f"(d[43]), "+f"(d[44]), "+f"(d[45]), "+f"(d[46]), "+f"(d[47]),
      "+f"(d[48]), "+f"(d[49]), "+f"(d[50]), "+f"(d[51]), "+f"(d[52]), "+f"(d[53]), "+f"(d[54]), "+f"(d[55]),
      "+f"(d[56]), "+f"(d[57]), "+f"(d[58]), "+f"(d[59]), "+f"(d[60]), "+f"(d[61]), "+f"(d[62]), "+f"(d[63])
    : "r"(a0), "r"(a1), "r"(a2), "r"(a3), "r"(db), "r"(scale_d), "n"(TB));
}
template <int TB>
__device__ __forceinline__ void wgmma_ss_n176(float (&d)[88], uint32_t da, uint32_t db, int scale_d) {
  asm volatile("{\n.reg .pred p;\n.reg .b64 da, db;\nsetp.ne.b32 p, %90, 0;\nmov.b64 da, {%88, 0x40000040};\nmov.b64 db, {%89, 0x40000040};\n"
    "wgmma.mma_async.sync.aligned.m64n176k16.f32.bf16.bf16 "
    "{%0, %1, %2, %3, %4, %5, %6, %7, %8, %9, %10, %11, %12, %13, %14, %15, "
    "%16, %17, %18, %19, %20, %21, %22, %23, %24, %25, %26, %27, %28, %29, %30, %31, "
    "%32, %33, %34, %35, %36, %37, %38, %39, %40, %41, %42, %43, %44, %45, %46, %47, "
    "%48, %49, %50, %51, %52, %53, %54, %55, %56, %57, %58, %59, %60, %61, %62, %63, "
    "%64, %65, %66, %67, %68, %69, %70, %71, %72, %73, %74, %75, %76, %77, %78, %79, "
    "%80, %81, %82, %83, %84, %85, %86, %87}, "
    "da, db, p, 1, 1, 0, %91;\n}\n"
    :
      "+f"(d[0]), "+f"(d[1]), "+f"(d[2]), "+f"(d[3]), "+f"(d[4]), "+f"(d[5]), "+f"(d[6]), "+f"(d[7]),
      "+f"(d[8]), "+f"(d[9]), "+f"(d[10]), "+f"(d[11]), "+f"(d[12]), "+f"(d[13]), "+f"(d[14]), "+f"(d[15]),
      "+f"(d[16]), "+f"(d[17]), "+f"(d[18]), "+f"(d[19]), "+f"(d[20]), "+f"(d[21]), "+f"(d[22]), "+f"(d[23]),
      "+f"(d[24]), "+f"(d[25]), "+f"(d[26]), "+f"(d[27]), "+f"(d[28]), "+f"(d[29]), "+f"(d[30]), "+f"(d[31]),
      "+f"(d[32]), "+f"(d[33]), "+f"(d[34]), "+f"(d[35]), "+f"(d[36]), "+f"(d[37]), "+f"(d[38]), "+f"(d[39]),
      "+f"(d[40]), "+f"(d[41]), "+f"(d[42]), "+f"(d[43]), "+f"(d[44]), "+f"(d[45]), "+f"(d[46]), "+f"(d[47]),
      "+f"(d[48]), "+f"(d[49]), "+f"(d[50]), "+f"(d[51]), "+f"(d[52]), "+f"(d[53]), "+f"(d[54]), "+f"(d[55]),
      "+f"(d[56]), "+f"(d[57]), "+f"(d[58]), "+f"(d[59]), "+f"(d[60]), "+f"(d[61]), "+f"(d[62]), "+f"(d[63]),
      "+f"(d[64]), "+f"(d[65]), "+f"(d[66]), "+f"(d[67]), "+f"(d[68]), "+f"(d[69]), "+f"(d[70]), "+f"(d[71]),
      "+f"(d[72]), "+f"(d[73]), "+f"(d[74]), "+f"(d[75]), "+f"(d[76]), "+f"(d[77]), "+f"(d[78]), "+f"(d[79]),
      "+f"(d[80]), "+f"(d[81]), "+f"(d[82]), "+f"(d[83]), "+f"(d[84]), "+f"(d[85]), "+f"(d[86]), "+f"(d[87])
    : "r"(da), "r"(db), "r"(scale_d), "n"(TB));
}
template <int TB>
__device__ __forceinline__ void wgmma_ss_n256(float (&d)[128], uint32_t da, uint32_t db, int scale_d) {
  asm volatile("{\n.reg .pred p;\n.reg .b64 da, db;\nsetp.ne.b32 p, %130, 0;\nmov.b64 da, {%128, 0x40000040};\nmov.b64 db, {%129, 0x40000040};\n"
    "wgmma.mma_async.sync.aligned.m64n256k16.f32.bf16.bf16 "
    "{%0, %1, %2, %3, %4, %5, %6, %7, %8, %9, %10, %11, %12, %13, %14, %15, "
    "%16, %17, %18, %19, %20, %21, %22, %23, %24, %25, %26, %27, %28, %29, %30, %31, "
    "%32, %33, %34, %35, %36, %37, %38, %39, %40, %41, %42, %43, %44, %45, %46, %47, "
    "%48, %49, %50, %51, %52, %53, %54, %55, %56, %57, %58, %59, %60, %61, %62, %63, "
    "%64, %65, %66, %67, %68, %69, %70, %71, %72, %73, %74, %75, %76, %77, %78, %79, "
    "%80, %81, %82, %83, %84, %85, %86, %87, %88, %89, %90, %91, %92, %93, %94, %95, "
    "%96, %97, %98, %99, %100, %101, %102, %103, %104, %105, %106, %107, %108, %109, %110, %111, "
    "%112, %113, %114, %115, %116, %117, %118, %119, %120, %121, %122, %123, %124, %125, %126, %127}, "
    "da, db, p, 1, 1, 0, %131;\n}\n"
    :
      "+f"(d[0]), "+f"(d[1]), "+f"(d[2]), "+f"(d[3]), "+f"(d[4]), "+f"(d[5]), "+f"(d[6]), "+f"(d[7]),
      "+f"(d[8]), "+f"(d[9]), "+f"(d[10]), "+f"(d[11]), "+f"(d[12]), "+f"(d[13]), "+f"(d[14]), "+f"(d[15]),
      "+f"(d[16]), "+f"(d[17]), "+f"(d[18]), "+f"(d[19]), "+f"(d[20]), "+f"(d[21]), "+f"(d[22]), "+f"(d[23]),
      "+f"(d[24]), "+f"(d[25]), "+f"(d[26]), "+f"(d[27]), "+f"(d[28]), "+f"(d[29]), "+f"(d[30]), "+f"(d[31]),
      "+f"(d[32]), "+f"(d[33]), "+f"(d[34]), "+f"(d[35]), "+f"(d[36]), "+f"(d[37]), "+f"(d[38]), "+f"(d[39]),
      "+f"(d[40]), "+f"(d[41]), "+f"(d[42]), "+f"(d[43]), "+f"(d[44]), "+f"(d[45]), "+f"(d[46]), "+f"(d[47]),
      "+f"(d[48]), "+f"(d[49]), "+f"(d[50]), "+f"(d[51]), "+f"(d[52]), "+f"(d[53]), "+f"(d[54]), "+f"(d[55]),
      "+f"(d[56]), "+f"(d[57]), "+f"(d[58]), "+f"(d[59]), "+f"(d[60]), "+f"(d[61]), "+f"(d[62]), "+f"(d[63]),
      "+f"(d[64]), "+f"(d[65]), "+f"(d[66]), "+f"(d[67]), "+f"(d[68]), "+f"(d[69]), "+f"(d[70]), "+f"(d[71]),
      "+f"(d[72]), "+f"(d[73]), "+f"(d[74]), "+f"(d[75]), "+f"(d[76]), "+f"(d[77]), "+f"(d[78]), "+f"(d[79]),
      "+f"(d[80]), "+f"(d[81]), "+f"(d[82]), "+f"(d[83]), "+f"(d[84]), "+f"(d[85]), "+f"(d[86]), "+f"(d[87]),
      "+f"(d[88]), "+f"(d[89]), "+f"(d[90]), "+f"(d[91]), "+f"(d[92]), "+f"(d[93]), "+f"(d[94]), "+f"(d[95]),
      "+f"(d[96]), "+f"(d[97]), "+f"(d[98]), "+f"(d[99]), "+f"(d[100]), "+f"(d[101]), "+f"(d[102]), "+f"(d[103]),
      "+f"(d[104]), "+f"(d[105]), "+f"(d[106]), "+f"(d[107]), "+f"(d[108]), "+f"(d[109]), "+f"(d[110]), "+f"(d[111]),
      "+f"(d[112]), "+f"(d[113]), "+f"(d[114]), "+f"(d[115]), "+f"(d[116]), "+f"(d[117]), "+f"(d[118]), "+f"(d[119]),
      "+f"(d[120]), "+f"(d[121]), "+f"(d[122]), "+f"(d[123]), "+f"(d[124]), "+f"(d[125]), "+f"(d[126]), "+f"(d[127])
    : "r"(da), "r"(db), "r"(scale_d), "n"(TB));
}
constexpr int KV_STAGES = 4;
constexpr int KV_STAGE_BYTES = 16384 + 32768;
constexpr int KV_SMEM = KV_STAGES * KV_STAGE_BYTES + 1024 + 256;

__device__ __forceinline__ void st_global_v4(void* p, uint32_t a, uint32_t b, uint32_t c, uint32_t d) {
  asm volatile("st.global.v4.b32 [%0], {%1, %2, %3, %4};" ::"l"(p), "r"(a), "r"(b), "r"(c), "r"(d) : "memory");
}

__device__ __forceinline__ int tile_matrix(int t, int c) { return (t == 2 || t == 5) ? 2 : (c >> 2); }
__device__ __forceinline__ int tile_pair(int t, int c) {
  if (t == 2) return 8 + c;
  if (t == 5) return c;
  const int group = t == 0 ? 3 : t == 1 ? 2 : t == 3 ? 1 : 0;
  return group * 4 + (c & 3);
}

__global__ void __launch_bounds__(384, 1)
qkv_kernel(const __grid_constant__ CUtensorMap mCkv, const __grid_constant__ CUtensorMap mXn, const __grid_constant__ CUtensorMap mWk,
           const __grid_constant__ CUtensorMap mWv, const __grid_constant__ CUtensorMap mWq, const bf16* __restrict__ x,
           const bf16* __restrict__ w_gate, const bf16* __restrict__ w_up) {
  extern __shared__ uint8_t smem_raw[];
  const uint32_t base = align1024(smem_u32(smem_raw));
  const uint32_t bars = base + KV_STAGES * KV_STAGE_BYTES;
  if (threadIdx.x == 0) {
    for (int i = 0; i < KV_STAGES; i++) {
      mbar_init(bars + i * 8, 1);
      mbar_init(bars + 64 + i * 8, 2);
    }
    asm volatile("fence.mbarrier_init.release.cluster;" ::: "memory");
  }
  if (threadIdx.x == 32) {
    tma_prefetch_desc(&mCkv);
    tma_prefetch_desc(&mWk);
    tma_prefetch_desc(&mWv);
    tma_prefetch_desc(&mXn);
    tma_prefetch_desc(&mWq);
  }
  if (blockIdx.x == 0 && threadIdx.x < 64) g_team[threadIdx.x] = 0;
  __syncthreads();
  pdl_launch();
  const int mblk = blockIdx.x & 15, ngrp = blockIdx.x >> 4;
  const int wg = threadIdx.x >> 7, warp = (threadIdx.x >> 5) & 3, lane = threadIdx.x & 31;
  if (wg == 0) {
    reg_dec<56>();
    if (warp == 0) {
      if (lane == 0) {
        for (int it = 0; it < 48; it++) {
          const int t = it >> 3, k = it & 7, st = it & 3;
          const int mat = tile_matrix(t, ngrp), pair = tile_pair(t, ngrp);
          if (it == 16) {
            spin_until(g_ln_count + mblk, 24);
            asm volatile("fence.proxy.async.global;" ::: "memory");
          }
          mbar_wait(bars + 64 + st * 8, ((it >> 2) & 1) ^ 1);
          const uint32_t sa = base + st * KV_STAGE_BYTES;
          mbar_expect_tx(bars + st * 8, KV_STAGE_BYTES);
          tma_load_2d(sa, mat == 2 ? &mXn : &mCkv, k * 64, mblk * 128, bars + st * 8);
          tma_load_3d(sa + 16384, mat == 0 ? &mWk : mat == 1 ? &mWv : &mWq, 0, k * 64, pair * 4, bars + st * 8);
        }
      }
    } else {
      {
        auto ld = [&](int r, uint4& v0, uint4& v1) {
          const uint4* src = reinterpret_cast<const uint4*>(x + (size_t)(blockIdx.x * 16 + r) * DM);
          v0 = __ldg(src + lane);
          v1 = __ldg(src + 32 + lane);
        };
        uint4 a0, a1, b0, b1;
        int r = warp - 1;
        ld(r, a0, a1);
        ld(r + 3, b0, b1);
        for (; r < 16; r += 3) {
          const uint32_t u[8] = {a0.x, a0.y, a0.z, a0.w, a1.x, a1.y, a1.z, a1.w};
          a0 = b0;
          a1 = b1;
          if (r + 6 < 16) ld(r + 6, b0, b1);
          float f[16];
          float s = 0.f;
#pragma unroll
          for (int i = 0; i < 8; i++) { f[2 * i] = bf_lo(u[i]); f[2 * i + 1] = bf_hi(u[i]); s += f[2 * i] + f[2 * i + 1]; }
#pragma unroll
          for (int o = 16; o > 0; o >>= 1) s += __shfl_xor_sync(0xffffffffu, s, o);
          const float mean = s * (1.f / DM);
          float q = 0.f;
#pragma unroll
          for (int i = 0; i < 16; i++) { f[i] -= mean; q += f[i] * f[i]; }
#pragma unroll
          for (int o = 16; o > 0; o >>= 1) q += __shfl_xor_sync(0xffffffffu, q, o);
          const float rstd = (0.08838834764831845f * 1.4426950408889634f) / sqrtf(q * (1.f / DM) + 1e-5f);
          uint4* dst = reinterpret_cast<uint4*>(g_xn + (size_t)(blockIdx.x * 16 + r) * DM);
          dst[lane] = make_uint4(pack_bf16(f[0] * rstd, f[1] * rstd), pack_bf16(f[2] * rstd, f[3] * rstd),
                                 pack_bf16(f[4] * rstd, f[5] * rstd), pack_bf16(f[6] * rstd, f[7] * rstd));
          dst[32 + lane] = make_uint4(pack_bf16(f[8] * rstd, f[9] * rstd), pack_bf16(f[10] * rstd, f[11] * rstd),
                                      pack_bf16(f[12] * rstd, f[13] * rstd), pack_bf16(f[14] * rstd, f[15] * rstd));
        }
      }
      __threadfence();
      __syncwarp();
      if (lane == 0) atomicAdd(g_ln_count + (blockIdx.x >> 3), 1u);
      const int task = blockIdx.x * 3 + (warp - 1);
      if (task < 352) {
        const int mat = task / 176, grp = task % 176;
        float a[8];
#pragma unroll
        for (int i = 0; i < 8; i++) a[i] = 0.f;
        if (grp < FF / 8) {
          const bf16* w = (mat ? w_up : w_gate) + grp * 8;
#pragma unroll 4
          for (int r = lane; r < DM; r += 32) {
            const uint4 v = __ldg(reinterpret_cast<const uint4*>(w + (size_t)r * FF));
            a[0] += bf_lo(v.x); a[1] += bf_hi(v.x); a[2] += bf_lo(v.y); a[3] += bf_hi(v.y);
            a[4] += bf_lo(v.z); a[5] += bf_hi(v.z); a[6] += bf_lo(v.w); a[7] += bf_hi(v.w);
          }
#pragma unroll
          for (int i = 0; i < 8; i++)
#pragma unroll
            for (int o = 16; o > 0; o >>= 1) a[i] += __shfl_xor_sync(0xffffffffu, a[i], o);
        }
        if (lane == 0) {
          float4* dst = reinterpret_cast<float4*>(g_cs + mat * 1408 + grp * 8);
          dst[0] = make_float4(a[0], a[1], a[2], a[3]);
          dst[1] = make_float4(a[4], a[5], a[6], a[7]);
        }
      }
    }
  } else {
    reg_inc<224>();
    const int cw = wg - 1;
    const int tid = threadIdx.x & 127;
    if (cw == 1) bar_arrive(1, 256);
    float acc[128];
    uint32_t pk[64];
    const size_t thr_off = (size_t)(mblk * 128 + cw * 64 + warp * 16 + (lane >> 2)) * HD + (lane & 3) * 8;
    bf16* prev_out = nullptr;
    auto store_piece = [&](int i) {
      bf16* dst = prev_out + (size_t)(i >> 2) * SEQ * HD + (i & 3) * 32;
      st_global_v4(dst, pk[8 * i], pk[8 * i + 2], pk[8 * i + 4], pk[8 * i + 6]);
      st_global_v4(dst + 8 * HD, pk[8 * i + 1], pk[8 * i + 3], pk[8 * i + 5], pk[8 * i + 7]);
    };
    for (int t = 0; t < 6; t++) {
#pragma unroll
      for (int k = 0; k < 8; k++) {
        const int st = k & 3;
        mbar_wait(bars + st * 8, (k >> 2) & 1);
        const uint32_t sa = base + st * KV_STAGE_BYTES;
        const uint32_t da = make_desc(sa + cw * 8192, 16);
        const uint32_t db = make_desc(sa + 16384, 8192);
        bar_sync(1 + cw, 256);
        wgmma_fence();
#pragma unroll
        for (int kk = 0; kk < 4; kk++) wgmma_ss_n256<1>(acc, desc_add(da, kk * 32), desc_add(db, kk * 2048), (k | kk) != 0);
        wgmma_commit();
        bar_arrive(2 - cw, 256);
        if (t > 0) store_piece(k);
        if (k > 0) {
          wgmma_wait<1>();
          if (tid == 0) mbar_arrive(bars + 64 + ((k - 1) & 3) * 8);
        }
      }
      wgmma_wait<0>();
      if (tid == 0) mbar_arrive(bars + 64 + 3 * 8);
      fence_regs(acc);
      const int mat = tile_matrix(t, ngrp);
#pragma unroll
      for (int i = 0; i < 64; i++) pk[i] = pack_bf16(acc[2 * i], acc[2 * i + 1]);
      prev_out = (mat == 0 ? g_k : mat == 1 ? g_v : g_q) + thr_off + (size_t)(tile_pair(t, ngrp) * 2) * SEQ * HD;
    }
#pragma unroll
    for (int i = 0; i < 8; i++) store_piece(i);
  }
}
constexpr int AT_SLOTS = 7;
constexpr int AT_SMEM = AT_SLOTS * 32768 + 1024 + 256;
struct AttnSched {
  int start[134];
  int tile[NH * 16];
};

struct RingPos {
  int slot;
  uint32_t phase;
  __device__ __forceinline__ void next() {
    if (++slot == AT_SLOTS) { slot = 0; phase ^= 1; }
  }
};

constexpr float SM_ZERO = 32.f;
constexpr float SM_LIMIT = 1099511627776.f;

template <int NG, bool SUB>
__device__ __forceinline__ void exp_pack(const float (&s)[64], uint32_t (&p)[32], float m0, float m1, float& r0, float& r1) {
  float a0 = 0.f, a1 = 0.f, b0 = 0.f, b1 = 0.f;
#pragma unroll
  for (int i = 0; i < NG; i++) {
    const float e0 = ex2(SUB ? s[4 * i] - m0 : s[4 * i]), e1 = ex2(SUB ? s[4 * i + 1] - m0 : s[4 * i + 1]);
    const float e2 = ex2(SUB ? s[4 * i + 2] - m1 : s[4 * i + 2]), e3 = ex2(SUB ? s[4 * i + 3] - m1 : s[4 * i + 3]);
    a0 += e0;
    b0 += e1;
    a1 += e2;
    b1 += e3;
    p[2 * i] = pack_bf16(e0, e1);
    p[2 * i + 1] = pack_bf16(e2, e3);
  }
#pragma unroll
  for (int i = 2 * NG; i < 32; i++) p[i] = 0u;
  r0 = a0 + b0;
  r1 = a1 + b1;
}

__device__ __forceinline__ void refresh_max(const float (&s)[64], float (&o)[64], float& m0, float& m1, float& l0, float& l1) {
  float a0 = fmaxf(s[0], s[1]), a1 = fmaxf(s[2], s[3]), b0 = fmaxf(s[4], s[5]), b1 = fmaxf(s[6], s[7]);
#pragma unroll
  for (int i = 2; i < 16; i += 2) {
    a0 = fmaxf(a0, fmaxf(s[4 * i], s[4 * i + 1]));
    a1 = fmaxf(a1, fmaxf(s[4 * i + 2], s[4 * i + 3]));
    b0 = fmaxf(b0, fmaxf(s[4 * i + 4], s[4 * i + 5]));
    b1 = fmaxf(b1, fmaxf(s[4 * i + 6], s[4 * i + 7]));
  }
  a0 = fmaxf(a0, b0);
  a1 = fmaxf(a1, b1);
  a0 = fmaxf(a0, __shfl_xor_sync(0xffffffffu, a0, 1));
  a1 = fmaxf(a1, __shfl_xor_sync(0xffffffffu, a1, 1));
  a0 = fmaxf(a0, __shfl_xor_sync(0xffffffffu, a0, 2));
  a1 = fmaxf(a1, __shfl_xor_sync(0xffffffffu, a1, 2));
  a0 = fmaxf(a0, m0);
  a1 = fmaxf(a1, m1);
  const float sc0 = ex2(m0 - a0), sc1 = ex2(m1 - a1);
  m0 = a0;
  m1 = a1;
  l0 *= sc0;
  l1 *= sc1;
#pragma unroll
  for (int i = 0; i < 16; i++) {
    o[4 * i] *= sc0;
    o[4 * i + 1] *= sc0;
    o[4 * i + 2] *= sc1;
    o[4 * i + 3] *= sc1;
  }
}

__device__ __forceinline__ void mask_diag(float (&s)[64], int cw, int warp, int lane) {
  const int t0 = cw * 64 + warp * 16 + (lane >> 2) - (lane & 3) * 2;
#pragma unroll
  for (int i = 0; i < 16; i++) {
    if (8 * i > t0) s[4 * i] = -INFINITY;
    if (8 * i + 1 > t0) s[4 * i + 1] = -INFINITY;
    if (8 * (i - 1) > t0) s[4 * i + 2] = -INFINITY;
    if (8 * (i - 1) + 1 > t0) s[4 * i + 3] = -INFINITY;
  }
}

__device__ __forceinline__ void load_q_frags(uint32_t (&q)[32], uint32_t sq, int cw, int warp, int lane) {
  const int row = cw * 64 + warp * 16 + (lane & 7) + ((lane >> 3) & 1) * 8;
  const uint32_t rbase = sq + row * 128;
#pragma unroll
  for (int j = 0; j < 8; j++) {
    const int chunk = (2 * j + (lane >> 4)) & 7;
    asm volatile("ldmatrix.sync.aligned.m8n8.x4.shared.b16 {%0, %1, %2, %3}, [%4];"
                 : "=r"(q[4 * j]), "=r"(q[4 * j + 1]), "=r"(q[4 * j + 2]), "=r"(q[4 * j + 3])
                 : "r"(rbase + (j >> 2) * 16384 + ((chunk ^ (row & 7)) << 4)) : "memory");
  }
}

__device__ __forceinline__ void row_recip(float l0, float l1, float& i0, float& i1) {
  l0 += __shfl_xor_sync(0xffffffffu, l0, 1);
  l1 += __shfl_xor_sync(0xffffffffu, l1, 1);
  l0 += __shfl_xor_sync(0xffffffffu, l0, 2);
  l1 += __shfl_xor_sync(0xffffffffu, l1, 2);
  asm("rcp.approx.ftz.f32 %0, %1;" : "=f"(i0) : "f"(l0));
  asm("rcp.approx.ftz.f32 %0, %1;" : "=f"(i1) : "f"(l1));
}
__device__ __forceinline__ void write_ctx(const float (&o)[64], float i0, float i1, bf16* dst) {
#pragma unroll
  for (int a = 0; a < 4; a++) {
    st_global_v4(dst + 32 * a, pack_bf16(o[16 * a] * i0, o[16 * a + 1] * i0), pack_bf16(o[16 * a + 4] * i0, o[16 * a + 5] * i0),
                 pack_bf16(o[16 * a + 8] * i0, o[16 * a + 9] * i0), pack_bf16(o[16 * a + 12] * i0, o[16 * a + 13] * i0));
    st_global_v4(dst + 32 * a + 8 * HD, pack_bf16(o[16 * a + 2] * i1, o[16 * a + 3] * i1), pack_bf16(o[16 * a + 6] * i1, o[16 * a + 7] * i1),
                 pack_bf16(o[16 * a + 10] * i1, o[16 * a + 11] * i1), pack_bf16(o[16 * a + 14] * i1, o[16 * a + 15] * i1));
  }
}

__global__ void __launch_bounds__(384, 1)
attn_kernel(const __grid_constant__ CUtensorMap mQ, const __grid_constant__ CUtensorMap mK, const __grid_constant__ CUtensorMap mV,
            const __grid_constant__ AttnSched sched) {
  extern __shared__ uint8_t smem_raw[];
  const uint32_t base = align1024(smem_u32(smem_raw));
  const uint32_t bar_full = base + AT_SLOTS * 32768, bar_empty = bar_full + 64;
  if (threadIdx.x == 0) {
    for (int i = 0; i < AT_SLOTS; i++) {
      mbar_init(bar_full + i * 8, 1);
      mbar_init(bar_empty + i * 8, 8);
    }
    asm volatile("fence.mbarrier_init.release.cluster;" ::: "memory");
  }
  if (threadIdx.x == 32) {
    tma_prefetch_desc(&mQ);
    tma_prefetch_desc(&mK);
    tma_prefetch_desc(&mV);
  }
  __syncthreads();
  pdl_launch();
  const int wg = threadIdx.x >> 7, warp = (threadIdx.x >> 5) & 3, lane = threadIdx.x & 31;
  const int t_begin = sched.start[blockIdx.x], t_end = sched.start[blockIdx.x + 1];
  if (wg == 0) {
    reg_dec<24>();
    if (warp == 0 && lane == 0) {
      RingPos rp{0, 1};
      auto load = [&](const CUtensorMap* m, int row) {
        mbar_wait(bar_empty + rp.slot * 8, rp.phase);
        const uint32_t dst = base + rp.slot * 32768, fb = bar_full + rp.slot * 8;
        mbar_expect_tx(fb, 32768);
        tma_load_2d(dst, m, 0, row, fb);
        tma_load_2d(dst + 16384, m, 64, row, fb);
        rp.next();
      };
      pdl_wait();
      int prev_v = -1;
      for (int ti = t_begin; ti < t_end; ti++) {
        const int tile = sched.tile[ti], h = tile >> 4, qb = tile & 15;
        if (ti == t_begin) load(&mQ, h * SEQ + qb * 128);
        for (int j = qb; j >= 0; j--) {
          if (prev_v >= 0) load(&mV, prev_v);
          load(&mK, h * SEQ + j * 128);
          prev_v = h * SEQ + j * 128;
          if (j == 0 && ti + 1 < t_end) {
            const int nt = sched.tile[ti + 1];
            load(&mQ, (nt >> 4) * SEQ + (nt & 15) * 128);
          }
        }
      }
      if (prev_v >= 0) load(&mV, prev_v);
    }
  } else {
    reg_inc<240>();
    const int cw = wg - 1;
    const int tid = threadIdx.x & 127;
    RingPos rp{0, 0};
    auto take = [&](int& slot) {
      mbar_wait(bar_full + rp.slot * 8, rp.phase);
      slot = rp.slot;
      rp.next();
    };
    auto release = [&](int slot) {
      if (lane == 0) mbar_arrive(bar_empty + slot * 8);
    };
    if (t_begin < t_end) {
      if (cw == 1) bar_arrive(1, 256);
      float s[64], o[64];
      uint32_t q[32], p[32];
      float m0, m1, l0 = 0.f, l1 = 0.f;
      auto ctx_ptr = [&](int t) {
        return g_ctx + (size_t)((t >> 4) * SEQ + (t & 15) * 128 + cw * 64 + warp * 16 + (lane >> 2)) * HD + (lane & 3) * 8;
      };
      int slot_q = 0, slot_v = 0, slot_k = 0;
      auto issue_pv = [&](bool accumulate) {
        const uint32_t dv = make_desc(base + slot_v * 32768, 16384);
#pragma unroll
        for (int kk = 0; kk < 8; kk++)
          wgmma_rs_n128<1>(o, p[4 * kk], p[4 * kk + 1], p[4 * kk + 2], p[4 * kk + 3], desc_add(dv, kk * 2048), kk != 0 || accumulate);
      };
      auto issue_qk = [&]() {
        const uint32_t dk = make_desc(base + slot_k * 32768, 16);
#pragma unroll
        for (int kk = 0; kk < 8; kk++)
          wgmma_rs_n128<0>(s, q[4 * kk], q[4 * kk + 1], q[4 * kk + 2], q[4 * kk + 3],
                           desc_add(dk, (kk >> 2) * 16384 + (kk & 3) * 32), kk != 0);
      };
      auto take_next = [&](bool last_block, bool more_tiles) {
        if (last_block && more_tiles) take(slot_q);
        take(slot_v);
        if (!last_block || more_tiles) take(slot_k);
      };

      auto start_tile = [&]() {
        const float a0 = __shfl_sync(0xffffffffu, s[0], lane & 28), a1 = __shfl_sync(0xffffffffu, s[2], lane & 28);
        m0 = fabsf(a0) <= SM_ZERO ? 0.f : a0;
        m1 = fabsf(a1) <= SM_ZERO ? 0.f : a1;
        l0 = 0.f;
        l1 = 0.f;
        mask_diag(s, cw, warp, lane);
      };

      int ti = t_begin;
      int j = sched.tile[ti] & 15;
      take(slot_q);
      load_q_frags(q, base + slot_q * 32768, cw, warp, lane);
      release(slot_q);
      take(slot_k);
      bar_sync(1 + cw, 256);
      wgmma_fence();
      issue_qk();
      wgmma_commit();
      bar_arrive(2 - cw, 256);
      int done_k = slot_k;
      bool more = ti + 1 < t_end;
      take_next(j == 0, more);
#pragma unroll
      for (int i = 0; i < 64; i++) o[i] = 0.f;
      wgmma_wait<0>();
      release(done_k);
      fence_regs(s);
      start_tile();
      bool fresh = true;
#pragma unroll 1
      while (true) {
        float r0, r1;
        bool general = !__all_sync(0xffffffffu, m0 == 0.f && m1 == 0.f), refresh = false;
        if (!general) {
          exp_pack<16, false>(s, p, m0, m1, r0, r1);
          general = refresh = __any_sync(0xffffffffu, !(r0 <= SM_LIMIT && r1 <= SM_LIMIT));
        }
        if (general) {
#pragma unroll 1
          while (true) {
            if (refresh) refresh_max(s, o, m0, m1, l0, l1);
            exp_pack<16, true>(s, p, m0, m1, r0, r1);
            if (refresh || !__any_sync(0xffffffffu, !(r0 <= SM_LIMIT && r1 <= SM_LIMIT))) break;
            refresh = true;
          }
        }
        l0 += r0;
        l1 += r1;
        if (j == 0) {
          if (!more) break;
          load_q_frags(q, base + slot_q * 32768, cw, warp, lane);
          release(slot_q);
        }
        bar_sync(1 + cw, 256);
        wgmma_fence();
        issue_pv(!fresh);
        issue_qk();
        wgmma_commit();
        bar_arrive(2 - cw, 256);
        const int done_v = slot_v;
        done_k = slot_k;
        fresh = j == 0;
        if (fresh) {
          j = sched.tile[++ti] & 15;
          more = ti + 1 < t_end;
        } else {
          j--;
        }
        take_next(j == 0, more);
        float i0, i1;
        if (fresh) row_recip(l0, l1, i0, i1);
        wgmma_wait<0>();
        release(done_v);
        release(done_k);
        fence_regs(s);
        fence_regs(o);
        if (fresh) {
          write_ctx(o, i0, i1, ctx_ptr(sched.tile[ti - 1]));
          start_tile();
        }
      }
      bar_sync(1 + cw, 256);
      wgmma_fence();
      issue_pv(!fresh);
      wgmma_commit();
      bar_arrive(2 - cw, 256);
      float i0, i1;
      row_recip(l0, l1, i0, i1);
      wgmma_wait<0>();
      fence_regs(o);
      write_ctx(o, i0, i1, ctx_ptr(sched.tile[t_end - 1]));
    }
  }
}
constexpr int TL_XBUF = 196608;
constexpr int TL_CS = TL_XBUF + 32768;
constexpr int TL_BARS = TL_CS + 1408;
constexpr int TL_SMEM = TL_BARS + 192 + 1024;
constexpr int ACT_PITCH = 1408;

__device__ __forceinline__ void tma_load_5d(uint32_t dst, const CUtensorMap* map, int c0, int c4, uint32_t bar) {
  asm volatile("cp.async.bulk.tensor.5d.shared::cluster.global.mbarrier::complete_tx::bytes [%0], [%1, {%3, %4, %4, %4, %5}], [%2];"
               ::"r"(dst), "l"(map), "r"(bar), "r"(c0), "r"(0), "r"(c4) : "memory");
}
__device__ __forceinline__ uint32_t relu_mul_bf16x2(uint32_t g, uint32_t u) {
  uint32_t r;
  asm("{\n.reg .b32 t;\nmax.NaN.bf16x2 t, %1, %3;\nmul.rn.bf16x2 %0, t, %2;\n}" : "=r"(r) : "r"(g), "r"(u), "r"(0u));
  return r;
}
__device__ __forceinline__ void team_arrive(unsigned int* ctr) {
  asm volatile("fence.acq_rel.gpu;\nred.relaxed.gpu.global.add.u32 [%0], 1;" ::"l"(ctr) : "memory");
}
__device__ __forceinline__ void st_global_v2(void* p, uint32_t a, uint32_t b) {
  asm volatile("st.global.v2.b32 [%0], {%1, %2};" ::"l"(p), "r"(a), "r"(b));
}

template <int NSTEPS>
__device__ __forceinline__ void gemm_split_k(float (&acc)[64], uint32_t base, uint32_t bar_full, int cw, int tid) {
  const uint32_t bar_empty = bar_full + 32;
#pragma unroll 1
  for (int s = 0; s < NSTEPS; s++) {
    const int st = s & 3;
    mbar_wait(bar_full + st * 8, (s >> 2) & 1);
    const uint32_t sa = base + st * 49152;
    const uint32_t da = make_desc(sa + cw * 8192, 16);
    const uint32_t db = make_desc(sa + 16384 + cw * 8192, 16384);
    wgmma_fence();
#pragma unroll
    for (int i = 0; i < 4; i++) wgmma_ss_n128<1>(acc, desc_add(da, i * 32), desc_add(db, i * 2048), (s | i) != 0);
    wgmma_commit();
    if (s > 0) {
      wgmma_wait<1>();
      if (tid == 0) mbar_arrive(bar_empty + ((s - 1) & 3) * 8);
    }
  }
  wgmma_wait<0>();
  if (tid == 0) mbar_arrive(bar_empty + ((NSTEPS - 1) & 3) * 8);
  fence_regs(acc);
}

template <int CW>
__device__ __forceinline__ void reduce_add_residual_t(const float (&acc)[64], const uint32_t (&res)[16], uint32_t (&pk)[16], uint32_t xbuf,
                                                      int tid) {
  constexpr int SEND = CW ? 0 : 32, KEEP = CW ? 32 : 0;
  const uint32_t wr = xbuf + CW * 16384 + tid * 16, rd = xbuf + (CW ^ 1) * 16384 + tid * 16;
#pragma unroll
  for (int i = 0; i < 8; i++)
    asm volatile("st.shared.v4.f32 [%0], {%1, %2, %3, %4};" ::"r"(wr + i * 2048), "f"(acc[SEND + 4 * i]), "f"(acc[SEND + 4 * i + 1]),
                 "f"(acc[SEND + 4 * i + 2]), "f"(acc[SEND + 4 * i + 3]) : "memory");
  bar_sync(1, 256);
#pragma unroll
  for (int i = 0; i < 8; i++) {
    float4 t;
    asm volatile("ld.shared.v4.f32 {%0, %1, %2, %3}, [%4];" : "=f"(t.x), "=f"(t.y), "=f"(t.z), "=f"(t.w) : "r"(rd + i * 2048) : "memory");
    const uint32_t p0 = pack_bf16(t.x + acc[KEEP + 4 * i], t.y + acc[KEEP + 4 * i + 1]);
    const uint32_t p1 = pack_bf16(t.z + acc[KEEP + 4 * i + 2], t.w + acc[KEEP + 4 * i + 3]);
    pk[2 * i] = pack_bf16(bf_lo(p0) + bf_lo(res[2 * i]), bf_hi(p0) + bf_hi(res[2 * i]));
    pk[2 * i + 1] = pack_bf16(bf_lo(p1) + bf_lo(res[2 * i + 1]), bf_hi(p1) + bf_hi(res[2 * i + 1]));
  }
}
__device__ __forceinline__ void reduce_add_residual(const float (&acc)[64], const uint32_t (&res)[16], uint32_t (&pk)[16], uint32_t xbuf,
                                                    int cw, int tid) {
  if (cw == 0) reduce_add_residual_t<0>(acc, res, pk, xbuf, tid);
  else reduce_add_residual_t<1>(acc, res, pk, xbuf, tid);
}

__global__ void __launch_bounds__(384, 1)
tail_kernel(const __grid_constant__ CUtensorMap mCtx, const __grid_constant__ CUtensorMap mWo, const __grid_constant__ CUtensorMap mH,
            const __grid_constant__ CUtensorMap mWg, const __grid_constant__ CUtensorMap mWu, const __grid_constant__ CUtensorMap mAct,
            const __grid_constant__ CUtensorMap mWd, const __grid_constant__ CUtensorMap mOut, const bf16* __restrict__ x) {
  extern __shared__ uint8_t smem_raw[];
  const uint32_t base = align1024(smem_u32(smem_raw));
  const uint32_t barC = base + TL_BARS, barD = barC + 64, barE = barD + 64;
  if (threadIdx.x == 0) {
    for (int i = 0; i < 12; i++) {
      mbar_init(barC + (i >> 2) * 64 + (i & 3) * 8, 1);
      mbar_init(barC + (i >> 2) * 64 + 32 + (i & 3) * 8, 2);
    }
    asm volatile("fence.mbarrier_init.release.cluster;" ::: "memory");
  }
  if (threadIdx.x == 32) {
    tma_prefetch_desc(&mWo);
    tma_prefetch_desc(&mCtx);
    tma_prefetch_desc(&mWg);
    tma_prefetch_desc(&mWu);
    tma_prefetch_desc(&mH);
    tma_prefetch_desc(&mWd);
    tma_prefetch_desc(&mAct);
    tma_prefetch_desc(&mOut);
  }
  __syncthreads();
  const int team = blockIdx.x >> 3, member = blockIdx.x & 7;
  const int mhalf = member >> 2, nt = member & 3;
  const int m64 = team * 2 + mhalf;
  const int n0 = member * 176;
  const int wg = threadIdx.x >> 7, warp = (threadIdx.x >> 5) & 3, lane = threadIdx.x & 31;
  if (wg == 0) {
    reg_dec<40>();
    if (warp == 0 && lane == 0) {
      auto load_wo = [&](int s) {
        const uint32_t dst = base + (s & 3) * 49152, fb = barC + (s & 3) * 8;
        mbar_expect_tx(fb, 49152);
        tma_load_2d(dst + 16384, &mWo, nt * 128, s * 128, fb);
        tma_load_2d(dst + 32768, &mWo, nt * 128 + 64, s * 128, fb);
      };
      for (int s = 0; s < 4; s++) load_wo(s);
      pdl_wait();
      for (int s = 0; s < NH; s++) {
        const uint32_t dst = base + (s & 3) * 49152, fb = barC + (s & 3) * 8;
        if (s >= 4) {
          mbar_wait(barC + 32 + (s & 3) * 8, ((s >> 2) & 1) ^ 1);
          load_wo(s);
        }
        tma_load_2d(dst, &mCtx, 0, s * SEQ + m64 * 64, fb);
        tma_load_2d(dst + 8192, &mCtx, 64, s * SEQ + m64 * 64, fb);
      }
      for (int it = 0; it < 8; it++) {
        const int st = it % 3;
        if (it < 3) {
          if (it == 0) mbar_wait(barC + 32, 1);
          mbar_wait(barC + 32 + (it + 1) * 8, 1);
        } else {
          mbar_wait(barD + 32 + st * 8, ((it / 3) & 1) ^ 1);
        }
        const uint32_t dst = base + st * 65536, fb = barD + st * 8;
        mbar_expect_tx(fb, 65536);
#pragma unroll
        for (int c = 0; c < 3; c++) {
          tma_load_5d(dst + 16384 + c * 8192, &mWg, n0 + c * 64, it * 2, fb);
          tma_load_5d(dst + 40960 + c * 8192, &mWu, n0 + c * 64, it * 2, fb);
        }
        if (it == 2) {
          spin_until(g_team + team * 4, 16);
          asm volatile("fence.proxy.async.global;" ::: "memory");
          tma_load_2d(base, &mH, 0, team * 128, barD);
          tma_load_2d(base + 65536, &mH, 64, team * 128, barD + 8);
        }
        if (it >= 2) tma_load_2d(dst, &mH, it * 64, team * 128, fb);
      }
      for (int s = 0; s < 11; s++) {
        const int st = s & 3;
        if (s < 4) {
          if (s == 0) mbar_wait(barD + 32, 0);
          if (s == 1) mbar_wait(barD + 32 + 8, 0);
          if (s == 2) mbar_wait(barD + 32 + 16, 1);
        } else {
          mbar_wait(barE + 32 + st * 8, ((s >> 2) & 1) ^ 1);
        }
        const uint32_t dst = base + st * 49152, fb = barE + st * 8;
        mbar_expect_tx(fb, 49152);
        tma_load_5d(dst + 16384, &mWd, nt * 128, s * 8, fb);
        tma_load_5d(dst + 32768, &mWd, nt * 128 + 64, s * 8, fb);
        if (s == 3) {
          spin_until(g_team + team * 4 + 1, 16);
          asm volatile("fence.proxy.async.global;" ::: "memory");
          for (int i = 0; i < 3; i++) {
            tma_load_2d(base + i * 49152, &mAct, i * 128, m64 * 64, barE + i * 8);
            tma_load_2d(base + i * 49152 + 8192, &mAct, i * 128 + 64, m64 * 64, barE + i * 8);
          }
        }
        if (s >= 3) {
          tma_load_2d(dst, &mAct, s * 128, m64 * 64, fb);
          tma_load_2d(dst + 8192, &mAct, s * 128 + 64, m64 * 64, fb);
        }
      }
    } else if (warp == 1) {
      pdl_wait();
      if (blockIdx.x == 0 && lane < 16) g_ln_count[lane] = 0;
      for (int i = lane; i < 352; i += 32) {
        const float c = __ldcg(g_cs + (i / 176) * 1408 + n0 + (i % 176));
        asm volatile("st.shared.f32 [%0], %1;" ::"r"(base + TL_CS + i * 4), "f"(c) : "memory");
      }
      bar_arrive(4, 288);
    }
  } else {
    reg_inc<232>();
    const int cw = wg - 1;
    const int tid = threadIdx.x & 127;
    const uint32_t xbuf = base + TL_XBUF;
    uint32_t hk[16];
    const int row0 = m64 * 64 + warp * 16 + (lane >> 2);
    {
      const int col0 = nt * 128 + cw * 64 + (lane & 3) * 2;
      uint32_t res[16];
#pragma unroll
      for (int i = 0; i < 8; i++) {
        res[2 * i] = __ldg(reinterpret_cast<const uint32_t*>(x + (size_t)row0 * DM + col0 + 8 * i));
        res[2 * i + 1] = __ldg(reinterpret_cast<const uint32_t*>(x + (size_t)(row0 + 8) * DM + col0 + 8 * i));
      }
      float acc[64];
      gemm_split_k<NH>(acc, base, barC, cw, tid);
      reduce_add_residual(acc, res, hk, xbuf, cw, tid);
      bf16* const hp = g_h + (size_t)row0 * DM + nt * 128 + cw * 64 + (lane & 3) * 8;
#pragma unroll
      for (int a = 0; a < 2; a++) {
        st_global_v4(hp + 32 * a, hk[8 * a], hk[8 * a + 2], hk[8 * a + 4], hk[8 * a + 6]);
        st_global_v4(hp + 32 * a + 8 * DM, hk[8 * a + 1], hk[8 * a + 3], hk[8 * a + 5], hk[8 * a + 7]);
      }
      bar_sync(2 + cw, 128);
      if (tid == 0) team_arrive(g_team + team * 4);
      float s0 = 0.f, s1 = 0.f;
#pragma unroll
      for (int i = 0; i < 8; i++) {
        s0 += bf_lo(hk[2 * i]) + bf_hi(hk[2 * i]);
        s1 += bf_lo(hk[2 * i + 1]) + bf_hi(hk[2 * i + 1]);
      }
      s0 += __shfl_xor_sync(0xffffffffu, s0, 1); s1 += __shfl_xor_sync(0xffffffffu, s1, 1);
      s0 += __shfl_xor_sync(0xffffffffu, s0, 2); s1 += __shfl_xor_sync(0xffffffffu, s1, 2);
      const float mu0 = s0 * (1.f / 64), mu1 = s1 * (1.f / 64);
      float q0 = 0.f, q1 = 0.f;
#pragma unroll
      for (int i = 0; i < 8; i++) {
        const float a = bf_lo(hk[2 * i]) - mu0, b = bf_hi(hk[2 * i]) - mu0, c = bf_lo(hk[2 * i + 1]) - mu1, d = bf_hi(hk[2 * i + 1]) - mu1;
        q0 += a * a + b * b;
        q1 += c * c + d * d;
      }
      q0 += __shfl_xor_sync(0xffffffffu, q0, 1); q1 += __shfl_xor_sync(0xffffffffu, q1, 1);
      q0 += __shfl_xor_sync(0xffffffffu, q0, 2); q1 += __shfl_xor_sync(0xffffffffu, q1, 2);
      if ((lane & 3) == 0) {
        g_stats[row0 * 8 + nt * 2 + cw] = make_float2(mu0, q0);
        g_stats[(row0 + 8) * 8 + nt * 2 + cw] = make_float2(mu1, q1);
      }
      bar_sync(2 + cw, 128);
      if (tid == 0) team_arrive(g_team + team * 4 + 2);
    }
    {
      float ag[88], au[88];
      float mean[2], rstd[2];
      int st = 0, prev = 0;
      uint32_t ph = 0;
#pragma unroll 1
      for (int it = 0; it < 8; it++) {
        mbar_wait(barD + st * 8, ph);
        const uint32_t sa = base + st * 65536;
        const uint32_t da = make_desc(sa + cw * 8192, 16);
        const uint32_t dg = make_desc(sa + 16384, 8192);
        const uint32_t du = make_desc(sa + 40960, 8192);
        wgmma_fence();
#pragma unroll
        for (int kk = 0; kk < 4; kk++) {
          wgmma_ss_n176<1>(ag, desc_add(da, kk * 32), desc_add(dg, kk * 2048), (it | kk) != 0);
          wgmma_ss_n176<1>(au, desc_add(da, kk * 32), desc_add(du, kk * 2048), (it | kk) != 0);
        }
        wgmma_commit();
        if (it > 0) {
          wgmma_wait<1>();
          if (tid == 0) mbar_arrive(barD + 32 + prev * 8);
        }
        prev = st;
        if (++st == 3) { st = 0; ph ^= 1; }
      }
      if (tid == 0) spin_until(g_team + team * 4 + 2, 16);
      bar_sync(2 + cw, 128);
      const int drow = team * 128 + cw * 64 + warp * 16 + (lane >> 2);
#pragma unroll
      for (int r = 0; r < 2; r++) {
        const float4* sp = reinterpret_cast<const float4*>(g_stats + (drow + 8 * r) * 8);
        const float4 a = __ldcg(sp), b = __ldcg(sp + 1), c = __ldcg(sp + 2), d = __ldcg(sp + 3);
        const float mu = (a.x + a.z + b.x + b.z + c.x + c.z + d.x + d.z) * 0.125f;
        float m2 = a.y + a.w + b.y + b.w + c.y + c.w + d.y + d.w;
        m2 += 64.f * ((a.x - mu) * (a.x - mu) + (a.z - mu) * (a.z - mu) + (b.x - mu) * (b.x - mu) + (b.z - mu) * (b.z - mu) +
                      (c.x - mu) * (c.x - mu) + (c.z - mu) * (c.z - mu) + (d.x - mu) * (d.x - mu) + (d.z - mu) * (d.z - mu));
        mean[r] = mu;
        rstd[r] = 1.f / sqrtf(m2 * (1.f / DM) + 1e-5f);
      }
      bar_sync(4, 288);
      wgmma_wait<0>();
      if (tid == 0) mbar_arrive(barD + 32 + prev * 8);
      fence_regs(ag);
      fence_regs(au);
      bf16* const actp = g_act + (size_t)drow * ACT_PITCH + n0 + (lane & 3) * 4;
      uint32_t csb = base + TL_CS + (lane & 3) * 8;
      asm volatile("" : "+r"(csb)::"memory");
#pragma unroll
      for (int j = 0; j < 11; j++) {
        uint32_t o4[4];
#pragma unroll
        for (int hh = 0; hh < 2; hh++) {
          const int i = 2 * j + hh;
          float2 cg, cu;
          asm("ld.shared.v2.f32 {%0, %1}, [%2];" : "=f"(cg.x), "=f"(cg.y) : "r"(csb + i * 32));
          asm("ld.shared.v2.f32 {%0, %1}, [%2];" : "=f"(cu.x), "=f"(cu.y) : "r"(csb + 704 + i * 32));
#pragma unroll
          for (int r = 0; r < 2; r++) {
            const uint32_t g = pack_bf16(fmaf(-mean[r], cg.x, ag[4 * i + 2 * r]) * rstd[r], fmaf(-mean[r], cg.y, ag[4 * i + 2 * r + 1]) * rstd[r]);
            const uint32_t u = pack_bf16(fmaf(-mean[r], cu.x, au[4 * i + 2 * r]) * rstd[r], fmaf(-mean[r], cu.y, au[4 * i + 2 * r + 1]) * rstd[r]);
            o4[2 * hh + r] = relu_mul_bf16x2(g, u);
          }
        }
        st_global_v2(actp + j * 16, o4[0], o4[2]);
        st_global_v2(actp + j * 16 + 8 * ACT_PITCH, o4[1], o4[3]);
      }
      bar_sync(2 + cw, 128);
      if (tid == 0) team_arrive(g_team + team * 4 + 1);
    }
    {
      float acc[64];
      gemm_split_k<11>(acc, base, barE, cw, tid);
      uint32_t pk[16];
      reduce_add_residual(acc, hk, pk, xbuf, cw, tid);
      const uint32_t mystag = xbuf + (cw ^ 1) * 16384;
      bar_sync(2 + cw, 128);
      const int row = warp * 16 + (lane & 7) + ((lane >> 3) & 1) * 8;
#pragma unroll
      for (int j = 0; j < 4; j++) {
        const int chunk = 2 * j + (lane >> 4);
        stmatrix_x4(mystag + row * 128 + ((chunk ^ (row & 7)) << 4), pk[4 * j], pk[4 * j + 1], pk[4 * j + 2], pk[4 * j + 3]);
      }
      fence_async_smem();
      bar_sync(2 + cw, 128);
      if (tid == 0) {
        tma_store_2d(&mOut, mystag, nt * 128 + cw * 64, m64 * 64);
        bulk_commit();
        bulk_wait_read<0>();
      }
    }
  }
}
typedef CUresult (*EncodeTiledFn)(CUtensorMap*, CUtensorMapDataType, cuuint32_t, void*, const cuuint64_t*, const cuuint64_t*,
                                  const cuuint32_t*, const cuuint32_t*, CUtensorMapInterleave, CUtensorMapSwizzle,
                                  CUtensorMapL2promotion, CUtensorMapFloatOOBfill);

EncodeTiledFn encode_fn() {
  static EncodeTiledFn fn = nullptr;
  if (!fn) {
    void* p = nullptr;
    cudaDriverEntryPointQueryResult q;
    cudaGetDriverEntryPoint("cuTensorMapEncodeTiled", &p, cudaEnableDefault, &q);
    fn = (EncodeTiledFn)p;
  }
  return fn;
}

CUtensorMap map2d(const void* ptr, uint64_t inner, uint64_t outer, uint64_t pitch_elems, uint32_t box_inner, uint32_t box_outer,
                  CUtensorMapSwizzle sw = CU_TENSOR_MAP_SWIZZLE_128B) {
  CUtensorMap m;
  cuuint64_t dims[2] = {inner, outer};
  cuuint64_t strides[1] = {pitch_elems * 2};
  cuuint32_t box[2] = {box_inner, box_outer};
  cuuint32_t es[2] = {1, 1};
  encode_fn()(&m, CU_TENSOR_MAP_DATA_TYPE_BFLOAT16, 2, const_cast<void*>(ptr), dims, strides, box, es, CU_TENSOR_MAP_INTERLEAVE_NONE, sw,
              CU_TENSOR_MAP_L2_PROMOTION_L2_256B, CU_TENSOR_MAP_FLOAT_OOB_FILL_NONE);
  return m;
}

CUtensorMap map3d_chunks(const void* ptr, uint64_t rows, uint64_t cols, uint32_t box_rows, uint32_t chunks) {
  CUtensorMap m;
  cuuint64_t dims[3] = {64, rows, cols / 64};
  cuuint64_t strides[2] = {cols * 2, 128};
  cuuint32_t box[3] = {64, box_rows, chunks};
  cuuint32_t es[3] = {1, 1, 1};
  encode_fn()(&m, CU_TENSOR_MAP_DATA_TYPE_BFLOAT16, 3, const_cast<void*>(ptr), dims, strides, box, es, CU_TENSOR_MAP_INTERLEAVE_NONE,
              CU_TENSOR_MAP_SWIZZLE_128B, CU_TENSOR_MAP_L2_PROMOTION_L2_256B, CU_TENSOR_MAP_FLOAT_OOB_FILL_NONE);
  return m;
}

CUtensorMap map5d_perm32(const void* ptr, uint64_t rows, uint64_t cols, uint32_t groups) {
  CUtensorMap m;
  const cuuint64_t row = cols * 2;
  cuuint64_t dims[5] = {cols, 2, 4, 4, rows / 32};
  cuuint64_t strides[4] = {row, 8 * row, 2 * row, 32 * row};
  cuuint32_t box[5] = {64, 2, 4, 4, groups};
  cuuint32_t es[5] = {1, 1, 1, 1, 1};
  encode_fn()(&m, CU_TENSOR_MAP_DATA_TYPE_BFLOAT16, 5, const_cast<void*>(ptr), dims, strides, box, es, CU_TENSOR_MAP_INTERLEAVE_NONE,
              CU_TENSOR_MAP_SWIZZLE_128B, CU_TENSOR_MAP_L2_PROMOTION_L2_256B, CU_TENSOR_MAP_FLOAT_OOB_FILL_NONE);
  return m;
}
CUtensorMap map5d_perm16(const void* ptr, uint64_t rows, uint64_t cols, uint32_t groups) {
  CUtensorMap m;
  const cuuint64_t row = cols * 2;
  cuuint64_t dims[5] = {cols, 2, 2, 4, rows / 16};
  cuuint64_t strides[4] = {row, 8 * row, 2 * row, 16 * row};
  cuuint32_t box[5] = {64, 2, 2, 4, groups};
  cuuint32_t es[5] = {1, 1, 1, 1, 1};
  encode_fn()(&m, CU_TENSOR_MAP_DATA_TYPE_BFLOAT16, 5, const_cast<void*>(ptr), dims, strides, box, es, CU_TENSOR_MAP_INTERLEAVE_NONE,
              CU_TENSOR_MAP_SWIZZLE_128B, CU_TENSOR_MAP_L2_PROMOTION_L2_256B, CU_TENSOR_MAP_FLOAT_OOB_FILL_NONE);
  return m;
}

template <typename T> void* sym_addr(T& sym) {
  void* p = nullptr;
  cudaGetSymbolAddress(&p, sym);
  return p;
}

void build_schedule(AttnSched& s, int ncta) {
  static int lists[134][64];
  int cnt[134] = {0};
  float load[134] = {0};
  auto cost = [](int tile) { return (float)((tile & 15) + 1) + 0.65f; };
    constexpr int GROUP = 32;
  for (int g = 0; g < NH / GROUP; g++)
    for (int qb = 15; qb >= 0; qb--)
      for (int h = g * GROUP; h < (g + 1) * GROUP; h++) {
        int best = 0;
        for (int c = 1; c < ncta; c++)
          if (load[c] < load[best]) best = c;
        lists[best][cnt[best]++] = h * 16 + qb;
        load[best] += cost(h * 16 + qb);
      }
  for (int iter = 0; iter < 4000; iter++) {
    int hi = 0;
    for (int c = 1; c < ncta; c++)
      if (load[c] > load[hi]) hi = c;
    float best_max = load[hi] - 1e-3f;
    int bi = -1, bc = -1, bj = -1;
    for (int c = 0; c < ncta; c++) {
      if (c == hi) continue;
      for (int i = 0; i < cnt[hi]; i++) {
        const float ci = cost(lists[hi][i]);
        for (int j = 0; j < cnt[c]; j++) {
          if (lists[c][j] / (16 * GROUP) != lists[hi][i] / (16 * GROUP)) continue;
          const float cj = cost(lists[c][j]);
          const float m = fmaxf(load[hi] - ci + cj, load[c] - cj + ci);
          if (m < best_max) { best_max = m; bi = i; bc = c; bj = j; }
        }
      }
    }
    if (bi < 0) break;
    const int ti = lists[hi][bi], tj = lists[bc][bj];
    lists[hi][bi] = tj;
    lists[bc][bj] = ti;
    load[hi] += cost(tj) - cost(ti);
    load[bc] += cost(ti) - cost(tj);
  }
  int pos = 0;
  for (int c = 0; c < ncta; c++) {
    s.start[c] = pos;
    for (int i = 0; i < cnt[c]; i++) s.tile[pos++] = lists[c][i];
  }
  for (int c = ncta; c < 134; c++) s.start[c] = pos;
}

template <typename... KArgs, typename... Args>
void launch(void (*kern)(KArgs...), int grid, int smem, bool pdl, Args... args) {
  cudaLaunchConfig_t cfg = {};
  cfg.gridDim = dim3(grid);
  cfg.blockDim = dim3(384);
  cfg.dynamicSmemBytes = smem;
  cfg.stream = cudaStreamPerThread;
  cudaLaunchAttribute at[1];
  at[0].id = cudaLaunchAttributeProgrammaticStreamSerialization;
  at[0].val.programmaticStreamSerializationAllowed = 1;
  cfg.attrs = at;
  cfg.numAttrs = pdl ? 1 : 0;
  cudaLaunchKernelEx(&cfg, kern, KArgs(args)...);
}

}

extern "C" void kernel_launch(void* const* d_in, const int* in_sizes, int n_in, void* d_out, int out_size) {
  const bf16* x = (const bf16*)d_in[0];
  const bf16* ckv = (const bf16*)d_in[1];
  const bf16* wq = (const bf16*)d_in[2];
  const bf16* wuk = (const bf16*)d_in[3];
  const bf16* wuv = (const bf16*)d_in[4];
  const bf16* wo = (const bf16*)d_in[5];
  const bf16* wgate = (const bf16*)d_in[7];
  const bf16* wup = (const bf16*)d_in[8];
  const bf16* wdown = (const bf16*)d_in[9];
  bf16* out = (bf16*)d_out;

  static bool init = false;
  static AttnSched sched;
  static int nsm = 132;
  static void *p_xn, *p_q, *p_k, *p_v, *p_ctx, *p_h, *p_act;
  if (!init) {
    cudaFuncSetAttribute(qkv_kernel, cudaFuncAttributeMaxDynamicSharedMemorySize, KV_SMEM);
    cudaFuncSetAttribute(attn_kernel, cudaFuncAttributeMaxDynamicSharedMemorySize, AT_SMEM);
    cudaFuncSetAttribute(tail_kernel, cudaFuncAttributeMaxDynamicSharedMemorySize, TL_SMEM);
    int dev = 0;
    cudaGetDevice(&dev);
    cudaDeviceGetAttribute(&nsm, cudaDevAttrMultiProcessorCount, dev);
    if (nsm > 132) nsm = 132;
    build_schedule(sched, nsm);
    p_xn = sym_addr(g_xn); p_q = sym_addr(g_q); p_k = sym_addr(g_k); p_v = sym_addr(g_v); p_ctx = sym_addr(g_ctx); p_h = sym_addr(g_h); p_act = sym_addr(g_act);
    init = true;
  }

  const CUtensorMap mCkv = map2d(ckv, DM, SEQ, DM, 64, 128);
  const CUtensorMap mXn = map2d(p_xn, DM, SEQ, DM, 64, 128);
  const CUtensorMap mWk = map3d_chunks(wuk, DM, NH * HD, 64, 4);
  const CUtensorMap mWv = map3d_chunks(wuv, DM, NH * HD, 64, 4);
  const CUtensorMap mWq = map3d_chunks(wq, DM, NH * HD, 64, 4);
  launch(qkv_kernel, 128, KV_SMEM, false, mCkv, mXn, mWk, mWv, mWq, x, wgate, wup);

  const CUtensorMap mQ = map2d(p_q, HD, NH * SEQ, HD, 64, 128);
  const CUtensorMap mK = map2d(p_k, HD, NH * SEQ, HD, 64, 128);
  const CUtensorMap mV = map2d(p_v, HD, NH * SEQ, HD, 64, 128);
  launch(attn_kernel, nsm, AT_SMEM, true, mQ, mK, mV, sched);

  const CUtensorMap mCtx = map2d(p_ctx, HD, NH * SEQ, HD, 64, 64);
  const CUtensorMap mWo = map2d(wo, DM, NH * HD, DM, 64, 128);
  const CUtensorMap mH = map2d(p_h, DM, SEQ, DM, 64, 128);
  const CUtensorMap mWg = map5d_perm32(wgate, DM, FF, 2);
  const CUtensorMap mWu = map5d_perm32(wup, DM, FF, 2);
  const CUtensorMap mAct = map2d(p_act, ACT_PITCH, SEQ, ACT_PITCH, 64, 64);
  const CUtensorMap mWd = map5d_perm16(wdown, FF, DM, 8);
  const CUtensorMap mOut = map2d(out, DM, SEQ, DM, 64, 64);
  launch(tail_kernel, 128, TL_SMEM, true, mCtx, mWo, mH, mWg, mWu, mAct, mWd, mOut, x);
}
```

```cpp
#include <cuda_runtime.h>
#include <cuda_bf16.h>
#include <cuda.h>
#include <stdint.h>

#pragma nv_diag_suppress 549

namespace {

constexpr int SEQ = 2048, DM = 512, NH = 32, HD = 128, FF = 1376;
typedef __nv_bfloat16 bf16;

__device__ __align__(1024) bf16 g_xn[SEQ * DM];
__device__ __align__(1024) bf16 g_q[NH * SEQ * HD];
__device__ __align__(1024) bf16 g_k[NH * SEQ * HD];
__device__ __align__(1024) bf16 g_v[NH * SEQ * HD];
__device__ __align__(1024) bf16 g_ctx[NH * SEQ * HD];
__device__ __align__(1024) bf16 g_h[SEQ * DM];
__device__ __align__(1024) bf16 g_act[SEQ * 1408];
__device__ __align__(1024) float2 g_stats[SEQ * 8];
__device__ __align__(1024) float g_cs[2 * 1408];

__device__ unsigned int g_team[64];
__device__ unsigned int g_ln_count[16];

__device__ __forceinline__ uint32_t smem_u32(const void* p) { return (uint32_t)__cvta_generic_to_shared(p); }
__device__ __forceinline__ void mbar_init(uint32_t bar, uint32_t cnt) {
  asm volatile("mbarrier.init.shared::cta.b64 [%0], %1;" ::"r"(bar), "r"(cnt));
}
__device__ __forceinline__ void mbar_expect_tx(uint32_t bar, uint32_t bytes) {
  asm volatile("mbarrier.arrive.expect_tx.shared::cta.b64 _, [%0], %1;" ::"r"(bar), "r"(bytes) : "memory");
}
__device__ __forceinline__ void mbar_arrive(uint32_t bar) {
  asm volatile("mbarrier.arrive.shared::cta.b64 _, [%0];" ::"r"(bar) : "memory");
}
__device__ __forceinline__ void mbar_wait(uint32_t bar, uint32_t parity) {
  asm volatile(
      "{\n.reg .pred p;\n.reg .u32 c;\n"
      "mov.u32 c, 0;\n"
      "WAIT_LOOP:\n"
      "mbarrier.try_wait.parity.shared::cta.b64 p, [%0], %1;\n"
      "@p bra WAIT_DONE;\n"
      "add.u32 c, c, 1;\n"
      "setp.lt.u32 p, c, 0x400000;\n"
      "@p bra WAIT_LOOP;\n"
      "trap;\n"
      "WAIT_DONE:\n}"
      ::"r"(bar), "r"(parity) : "memory");
}
__device__ __forceinline__ void spin_until(const unsigned int* ctr, unsigned int target) {
  asm volatile(
      "{\n.reg .pred p;\n.reg .u32 c, v;\n"
      "mov.u32 c, 0;\n"
      "SPIN_LOOP:\n"
      "ld.acquire.gpu.global.u32 v, [%0];\n"
      "setp.ge.u32 p, v, %1;\n"
      "@p bra SPIN_DONE;\n"
      "add.u32 c, c, 1;\n"
      "setp.lt.u32 p, c, 0x1000000;\n"
      "@p bra SPIN_LOOP;\n"
      "trap;\n"
      "SPIN_DONE:\n}"
      ::"l"(ctr), "r"(target) : "memory");
}
__device__ __forceinline__ void tma_load_2d(uint32_t dst, const CUtensorMap* map, int c0, int c1, uint32_t bar) {
  asm volatile("cp.async.bulk.tensor.2d.shared::cluster.global.mbarrier::complete_tx::bytes [%0], [%1, {%3, %4}], [%2];"
               ::"r"(dst), "l"(map), "r"(bar), "r"(c0), "r"(c1) : "memory");
}
__device__ __forceinline__ void tma_load_3d(uint32_t dst, const CUtensorMap* map, int c0, int c1, int c2, uint32_t bar) {
  asm volatile("cp.async.bulk.tensor.3d.shared::cluster.global.mbarrier::complete_tx::bytes [%0], [%1, {%3, %4, %5}], [%2];"
               ::"r"(dst), "l"(map), "r"(bar), "r"(c0), "r"(c1), "r"(c2) : "memory");
}
__device__ __forceinline__ void tma_store_2d(const CUtensorMap* map, uint32_t src, int c0, int c1) {
  asm volatile("cp.async.bulk.tensor.2d.global.shared::cta.bulk_group [%0, {%2, %3}], [%1];"
               ::"l"(map), "r"(src), "r"(c0), "r"(c1) : "memory");
}
__device__ __forceinline__ void tma_prefetch_desc(const CUtensorMap* map) {
  asm volatile("prefetch.tensormap [%0];" ::"l"(map) : "memory");
}
__device__ __forceinline__ void bulk_commit() { asm volatile("cp.async.bulk.commit_group;" ::: "memory"); }
template <int N> __device__ __forceinline__ void bulk_wait_read() { asm volatile("cp.async.bulk.wait_group.read %0;" ::"n"(N) : "memory"); }
template <int N> __device__ __forceinline__ void bulk_wait() { asm volatile("cp.async.bulk.wait_group %0;" ::"n"(N) : "memory"); }
__device__ __forceinline__ void fence_async_smem() { asm volatile("fence.proxy.async.shared::cta;" ::: "memory"); }
__device__ __forceinline__ void bar_sync(int id, int n) { asm volatile("bar.sync %0, %1;" ::"r"(id), "r"(n) : "memory"); }
__device__ __forceinline__ void bar_arrive(int id, int n) { asm volatile("bar.arrive %0, %1;" ::"r"(id), "r"(n) : "memory"); }
__device__ __forceinline__ void pdl_wait() { asm volatile("griddepcontrol.wait;" ::: "memory"); }
__device__ __forceinline__ void pdl_launch() { asm volatile("griddepcontrol.launch_dependents;" ::: "memory"); }
template <int N> __device__ __forceinline__ void reg_inc() { asm volatile("setmaxnreg.inc.sync.aligned.u32 %0;" ::"n"(N)); }
template <int N> __device__ __forceinline__ void reg_dec() { asm volatile("setmaxnreg.dec.sync.aligned.u32 %0;" ::"n"(N)); }
__device__ __forceinline__ void wgmma_fence() { asm volatile("wgmma.fence.sync.aligned;" ::: "memory"); }
__device__ __forceinline__ void wgmma_commit() { asm volatile("wgmma.commit_group.sync.aligned;" ::: "memory"); }
template <int N> __device__ __forceinline__ void wgmma_wait() { asm volatile("wgmma.wait_group.sync.aligned %0;" ::"n"(N) : "memory"); }
template <int N> __device__ __forceinline__ void fence_regs(float (&r)[N]) {
#pragma unroll
  for (int i = 0; i < N; i++) asm volatile("" : "+f"(r[i])::"memory");
}
template <int N> __device__ __forceinline__ void fence_regs(uint32_t (&r)[N]) {
#pragma unroll
  for (int i = 0; i < N; i++) asm volatile("" : "+r"(r[i])::"memory");
}
__device__ __forceinline__ uint32_t make_desc(uint32_t addr, uint32_t lbo_bytes) { return ((addr & 0x3FFFF) >> 4) | ((lbo_bytes >> 4) << 16); }
__device__ __forceinline__ uint32_t desc_add(uint32_t d, uint32_t bytes) { return d + (bytes >> 4); }
__device__ __forceinline__ uint32_t pack_bf16(float lo, float hi) {
  uint32_t r;
  asm("cvt.rn.bf16x2.f32 %0, %1, %2;" : "=r"(r) : "f"(hi), "f"(lo));
  return r;
}
__device__ __forceinline__ float bf_lo(uint32_t v) { return __uint_as_float(v << 16); }
__device__ __forceinline__ float bf_hi(uint32_t v) { return __uint_as_float(v & 0xffff0000u); }
__device__ __forceinline__ float ex2(float x) {
  float y;
  asm("ex2.approx.ftz.f32 %0, %1;" : "=f"(y) : "f"(x));
  return y;
}
__device__ __forceinline__ void stmatrix_x4(uint32_t addr, uint32_t a, uint32_t b, uint32_t c, uint32_t d) {
  asm volatile("stmatrix.sync.aligned.m8n8.x4.shared.b16 [%0], {%1, %2, %3, %4};"
               ::"r"(addr), "r"(a), "r"(b), "r"(c), "r"(d) : "memory");
}
__device__ __forceinline__ uint32_t align1024(uint32_t a) { return (a + 1023u) & ~1023u; }

template <int TB>
__device__ __forceinline__ void wgmma_ss_n128(float (&d)[64], uint32_t da, uint32_t db, int scale_d) {
  asm volatile("{\n.reg .pred p;\n.reg .b64 da, db;\nsetp.ne.b32 p, %66, 0;\nmov.b64 da, {%64, 0x40000040};\nmov.b64 db, {%65, 0x40000040};\n"
    "wgmma.mma_async.sync.aligned.m64n128k16.f32.bf16.bf16 "
    "{%0, %1, %2, %3, %4, %5, %6, %7, %8, %9, %10, %11, %12, %13, %14, %15, "
    "%16, %17, %18, %19, %20, %21, %22, %23, %24, %25, %26, %27, %28, %29, %30, %31, "
    "%32, %33, %34, %35, %36, %37, %38, %39, %40, %41, %42, %43, %44, %45, %46, %47, "
    "%48, %49, %50, %51, %52, %53, %54, %55, %56, %57, %58, %59, %60, %61, %62, %63}, "
    "da, db, p, 1, 1, 0, %67;\n}\n"
    :
      "+f"(d[0]), "+f"(d[1]), "+f"(d[2]), "+f"(d[3]), "+f"(d[4]), "+f"(d[5]), "+f"(d[6]), "+f"(d[7]),
      "+f"(d[8]), "+f"(d[9]), "+f"(d[10]), "+f"(d[11]), "+f"(d[12]), "+f"(d[13]), "+f"(d[14]), "+f"(d[15]),
      "+f"(d[16]), "+f"(d[17]), "+f"(d[18]), "+f"(d[19]), "+f"(d[20]), "+f"(d[21]), "+f"(d[22]), "+f"(d[23]),
      "+f"(d[24]), "+f"(d[25]), "+f"(d[26]), "+f"(d[27]), "+f"(d[28]), "+f"(d[29]), "+f"(d[30]), "+f"(d[31]),
      "+f"(d[32]), "+f"(d[33]), "+f"(d[34]), "+f"(d[35]), "+f"(d[36]), "+f"(d[37]), "+f"(d[38]), "+f"(d[39]),
      "+f"(d[40]), "+f"(d[41]), "+f"(d[42]), "+f"(d[43]), "+f"(d[44]), "+f"(d[45]), "+f"(d[46]), "+f"(d[47]),
      "+f"(d[48]), "+f"(d[49]), "+f"(d[50]), "+f"(d[51]), "+f"(d[52]), "+f"(d[53]), "+f"(d[54]), "+f"(d[55]),
      "+f"(d[56]), "+f"(d[57]), "+f"(d[58]), "+f"(d[59]), "+f"(d[60]), "+f"(d[61]), "+f"(d[62]), "+f"(d[63])
    : "r"(da), "r"(db), "r"(scale_d), "n"(TB));
}
template <int TB>
__device__ __forceinline__ void wgmma_rs_n128(float (&d)[64], uint32_t a0, uint32_t a1, uint32_t a2, uint32_t a3, uint32_t db, int scale_d) {
  asm volatile("{\n.reg .pred p;\n.reg .b64 db;\nsetp.ne.b32 p, %69, 0;\nmov.b64 db, {%68, 0x40000040};\n"
    "wgmma.mma_async.sync.aligned.m64n128k16.f32.bf16.bf16 "
    "{%0, %1, %2, %3, %4, %5, %6, %7, %8, %9, %10, %11, %12, %13, %14, %15, "
    "%16, %17, %18, %19, %20, %21, %22, %23, %24, %25, %26, %27, %28, %29, %30, %31, "
    "%32, %33, %34, %35, %36, %37, %38, %39, %40, %41, %42, %43, %44, %45, %46, %47, "
    "%48, %49, %50, %51, %52, %53, %54, %55, %56, %57, %58, %59, %60, %61, %62, %63}, "
    "{%64, %65, %66, %67}, db, p, 1, 1, %70;\n}\n"
    :
      "+f"(d[0]), "+f"(d[1]), "+f"(d[2]), "+f"(d[3]), "+f"(d[4]), "+f"(d[5]), "+f"(d[6]), "+f"(d[7]),
      "+f"(d[8]), "+f"(d[9]), "+f"(d[10]), "+f"(d[11]), "+f"(d[12]), "+f"(d[13]), "+f"(d[14]), "+f"(d[15]),
      "+f"(d[16]), "+f"(d[17]), "+f"(d[18]), "+f"(d[19]), "+f"(d[20]), "+f"(d[21]), "+f"(d[22]), "+f"(d[23]),
      "+f"(d[24]), "+f"(d[25]), "+f"(d[26]), "+f"(d[27]), "+f"(d[28]), "+f"(d[29]), "+f"(d[30]), "+f"(d[31]),
      "+f"(d[32]), "+f"(d[33]), "+f"(d[34]), "+f"(d[35]), "+f"(d[36]), "+f"(d[37]), "+f"(d[38]), "+f"(d[39]),
      "+f"(d[40]), "+f"(d[41]), "+f"(d[42]), "+f"(d[43]), "+f"(d[44]), "+f"(d[45]), "+f"(d[46]), "+f"(d[47]),
      "+f"(d[48]), "+f"(d[49]), "+f"(d[50]), "+f"(d[51]), "+f"(d[52]), "+f"(d[53]), "+f"(d[54]), "+f"(d[55]),
      "+f"(d[56]), "+f"(d[57]), "+f"(d[58]), "+f"(d[59]), "+f"(d[60]), "+f"(d[61]), "+f"(d[62]), "+f"(d[63])
    : "r"(a0), "r"(a1), "r"(a2), "r"(a3), "r"(db), "r"(scale_d), "n"(TB));
}
template <int TB>
__device__ __forceinline__ void wgmma_ss_n176(float (&d)[88], uint32_t da, uint32_t db, int scale_d) {
  asm volatile("{\n.reg .pred p;\n.reg .b64 da, db;\nsetp.ne.b32 p, %90, 0;\nmov.b64 da, {%88, 0x40000040};\nmov.b64 db, {%89, 0x40000040};\n"
    "wgmma.mma_async.sync.aligned.m64n176k16.f32.bf16.bf16 "
    "{%0, %1, %2, %3, %4, %5, %6, %7, %8, %9, %10, %11, %12, %13, %14, %15, "
    "%16, %17, %18, %19, %20, %21, %22, %23, %24, %25, %26, %27, %28, %29, %30, %31, "
    "%32, %33, %34, %35, %36, %37, %38, %39, %40, %41, %42, %43, %44, %45, %46, %47, "
    "%48, %49, %50, %51, %52, %53, %54, %55, %56, %57, %58, %59, %60, %61, %62, %63, "
    "%64, %65, %66, %67, %68, %69, %70, %71, %72, %73, %74, %75, %76, %77, %78, %79, "
    "%80, %81, %82, %83, %84, %85, %86, %87}, "
    "da, db, p, 1, 1, 0, %91;\n}\n"
    :
      "+f"(d[0]), "+f"(d[1]), "+f"(d[2]), "+f"(d[3]), "+f"(d[4]), "+f"(d[5]), "+f"(d[6]), "+f"(d[7]),
      "+f"(d[8]), "+f"(d[9]), "+f"(d[10]), "+f"(d[11]), "+f"(d[12]), "+f"(d[13]), "+f"(d[14]), "+f"(d[15]),
      "+f"(d[16]), "+f"(d[17]), "+f"(d[18]), "+f"(d[19]), "+f"(d[20]), "+f"(d[21]), "+f"(d[22]), "+f"(d[23]),
      "+f"(d[24]), "+f"(d[25]), "+f"(d[26]), "+f"(d[27]), "+f"(d[28]), "+f"(d[29]), "+f"(d[30]), "+f"(d[31]),
      "+f"(d[32]), "+f"(d[33]), "+f"(d[34]), "+f"(d[35]), "+f"(d[36]), "+f"(d[37]), "+f"(d[38]), "+f"(d[39]),
      "+f"(d[40]), "+f"(d[41]), "+f"(d[42]), "+f"(d[43]), "+f"(d[44]), "+f"(d[45]), "+f"(d[46]), "+f"(d[47]),
      "+f"(d[48]), "+f"(d[49]), "+f"(d[50]), "+f"(d[51]), "+f"(d[52]), "+f"(d[53]), "+f"(d[54]), "+f"(d[55]),
      "+f"(d[56]), "+f"(d[57]), "+f"(d[58]), "+f"(d[59]), "+f"(d[60]), "+f"(d[61]), "+f"(d[62]), "+f"(d[63]),
      "+f"(d[64]), "+f"(d[65]), "+f"(d[66]), "+f"(d[67]), "+f"(d[68]), "+f"(d[69]), "+f"(d[70]), "+f"(d[71]),
      "+f"(d[72]), "+f"(d[73]), "+f"(d[74]), "+f"(d[75]), "+f"(d[76]), "+f"(d[77]), "+f"(d[78]), "+f"(d[79]),
      "+f"(d[80]), "+f"(d[81]), "+f"(d[82]), "+f"(d[83]), "+f"(d[84]), "+f"(d[85]), "+f"(d[86]), "+f"(d[87])
    : "r"(da), "r"(db), "r"(scale_d), "n"(TB));
}
template <int TB>
__device__ __forceinline__ void wgmma_ss_n256(float (&d)[128], uint32_t da, uint32_t db, int scale_d) {
  asm volatile("{\n.reg .pred p;\n.reg .b64 da, db;\nsetp.ne.b32 p, %130, 0;\nmov.b64 da, {%128, 0x40000040};\nmov.b64 db, {%129, 0x40000040};\n"
    "wgmma.mma_async.sync.aligned.m64n256k16.f32.bf16.bf16 "
    "{%0, %1, %2, %3, %4, %5, %6, %7, %8, %9, %10, %11, %12, %13, %14, %15, "
    "%16, %17, %18, %19, %20, %21, %22, %23, %24, %25, %26, %27, %28, %29, %30, %31, "
    "%32, %33, %34, %35, %36, %37, %38, %39, %40, %41, %42, %43, %44, %45, %46, %47, "
    "%48, %49, %50, %51, %52, %53, %54, %55, %56, %57, %58, %59, %60, %61, %62, %63, "
    "%64, %65, %66, %67, %68, %69, %70, %71, %72, %73, %74, %75, %76, %77, %78, %79, "
    "%80, %81, %82, %83, %84, %85, %86, %87, %88, %89, %90, %91, %92, %93, %94, %95, "
    "%96, %97, %98, %99, %100, %101, %102, %103, %104, %105, %106, %107, %108, %109, %110, %111, "
    "%112, %113, %114, %115, %116, %117, %118, %119, %120, %121, %122, %123, %124, %125, %126, %127}, "
    "da, db, p, 1, 1, 0, %131;\n}\n"
    :
      "+f"(d[0]), "+f"(d[1]), "+f"(d[2]), "+f"(d[3]), "+f"(d[4]), "+f"(d[5]), "+f"(d[6]), "+f"(d[7]),
      "+f"(d[8]), "+f"(d[9]), "+f"(d[10]), "+f"(d[11]), "+f"(d[12]), "+f"(d[13]), "+f"(d[14]), "+f"(d[15]),
      "+f"(d[16]), "+f"(d[17]), "+f"(d[18]), "+f"(d[19]), "+f"(d[20]), "+f"(d[21]), "+f"(d[22]), "+f"(d[23]),
      "+f"(d[24]), "+f"(d[25]), "+f"(d[26]), "+f"(d[27]), "+f"(d[28]), "+f"(d[29]), "+f"(d[30]), "+f"(d[31]),
      "+f"(d[32]), "+f"(d[33]), "+f"(d[34]), "+f"(d[35]), "+f"(d[36]), "+f"(d[37]), "+f"(d[38]), "+f"(d[39]),
      "+f"(d[40]), "+f"(d[41]), "+f"(d[42]), "+f"(d[43]), "+f"(d[44]), "+f"(d[45]), "+f"(d[46]), "+f"(d[47]),
      "+f"(d[48]), "+f"(d[49]), "+f"(d[50]), "+f"(d[51]), "+f"(d[52]), "+f"(d[53]), "+f"(d[54]), "+f"(d[55]),
      "+f"(d[56]), "+f"(d[57]), "+f"(d[58]), "+f"(d[59]), "+f"(d[60]), "+f"(d[61]), "+f"(d[62]), "+f"(d[63]),
      "+f"(d[64]), "+f"(d[65]), "+f"(d[66]), "+f"(d[67]), "+f"(d[68]), "+f"(d[69]), "+f"(d[70]), "+f"(d[71]),
      "+f"(d[72]), "+f"(d[73]), "+f"(d[74]), "+f"(d[75]), "+f"(d[76]), "+f"(d[77]), "+f"(d[78]), "+f"(d[79]),
      "+f"(d[80]), "+f"(d[81]), "+f"(d[82]), "+f"(d[83]), "+f"(d[84]), "+f"(d[85]), "+f"(d[86]), "+f"(d[87]),
      "+f"(d[88]), "+f"(d[89]), "+f"(d[90]), "+f"(d[91]), "+f"(d[92]), "+f"(d[93]), "+f"(d[94]), "+f"(d[95]),
      "+f"(d[96]), "+f"(d[97]), "+f"(d[98]), "+f"(d[99]), "+f"(d[100]), "+f"(d[101]), "+f"(d[102]), "+f"(d[103]),
      "+f"(d[104]), "+f"(d[105]), "+f"(d[106]), "+f"(d[107]), "+f"(d[108]), "+f"(d[109]), "+f"(d[110]), "+f"(d[111]),
      "+f"(d[112]), "+f"(d[113]), "+f"(d[114]), "+f"(d[115]), "+f"(d[116]), "+f"(d[117]), "+f"(d[118]), "+f"(d[119]),
      "+f"(d[120]), "+f"(d[121]), "+f"(d[122]), "+f"(d[123]), "+f"(d[124]), "+f"(d[125]), "+f"(d[126]), "+f"(d[127])
    : "r"(da), "r"(db), "r"(scale_d), "n"(TB));
}
constexpr int KV_STAGES = 4;
constexpr int KV_STAGE_BYTES = 16384 + 32768;
constexpr int KV_SMEM = KV_STAGES * KV_STAGE_BYTES + 1024 + 256;

__device__ __forceinline__ void st_global_v4(void* p, uint32_t a, uint32_t b, uint32_t c, uint32_t d) {
  asm volatile("st.global.v4.b32 [%0], {%1, %2, %3, %4};" ::"l"(p), "r"(a), "r"(b), "r"(c), "r"(d) : "memory");
}

__device__ __forceinline__ int tile_matrix(int t, int c) { return (t == 2 || t == 5) ? 2 : (c >> 2); }
__device__ __forceinline__ int tile_pair(int t, int c) {
  if (t == 2) return 8 + c;
  if (t == 5) return c;
  const int group = t == 0 ? 3 : t == 1 ? 2 : t == 3 ? 1 : 0;
  return group * 4 + (c & 3);
}

__global__ void __launch_bounds__(384, 1)
qkv_kernel(const __grid_constant__ CUtensorMap mCkv, const __grid_constant__ CUtensorMap mXn, const __grid_constant__ CUtensorMap mWk,
           const __grid_constant__ CUtensorMap mWv, const __grid_constant__ CUtensorMap mWq, const bf16* __restrict__ x,
           const bf16* __restrict__ w_gate, const bf16* __restrict__ w_up) {
  extern __shared__ uint8_t smem_raw[];
  const uint32_t base = align1024(smem_u32(smem_raw));
  const uint32_t bars = base + KV_STAGES * KV_STAGE_BYTES;
  if (threadIdx.x == 0) {
    for (int i = 0; i < KV_STAGES; i++) {
      mbar_init(bars + i * 8, 1);
      mbar_init(bars + 64 + i * 8, 2);
    }
    asm volatile("fence.mbarrier_init.release.cluster;" ::: "memory");
  }
  if (threadIdx.x == 32) {
    tma_prefetch_desc(&mCkv);
    tma_prefetch_desc(&mWk);
    tma_prefetch_desc(&mWv);
    tma_prefetch_desc(&mXn);
    tma_prefetch_desc(&mWq);
  }
  if (blockIdx.x == 0 && threadIdx.x < 64) g_team[threadIdx.x] = 0;
  __syncthreads();
  pdl_launch();
  const int mblk = blockIdx.x & 15, ngrp = blockIdx.x >> 4;
  const int wg = threadIdx.x >> 7, warp = (threadIdx.x >> 5) & 3, lane = threadIdx.x & 31;
  if (wg == 0) {
    reg_dec<56>();
    if (warp == 0) {
      if (lane == 0) {
        for (int it = 0; it < 48; it++) {
          const int t = it >> 3, k = it & 7, st = it & 3;
          const int mat = tile_matrix(t, ngrp), pair = tile_pair(t, ngrp);
          if (it == 16) {
            spin_until(g_ln_count + mblk, 24);
            asm volatile("fence.proxy.async.global;" ::: "memory");
          }
          mbar_wait(bars + 64 + st * 8, ((it >> 2) & 1) ^ 1);
          const uint32_t sa = base + st * KV_STAGE_BYTES;
          mbar_expect_tx(bars + st * 8, KV_STAGE_BYTES);
          tma_load_2d(sa, mat == 2 ? &mXn : &mCkv, k * 64, mblk * 128, bars + st * 8);
          tma_load_3d(sa + 16384, mat == 0 ? &mWk : mat == 1 ? &mWv : &mWq, 0, k * 64, pair * 4, bars + st * 8);
        }
      }
    } else {
      {
        auto ld = [&](int r, uint4& v0, uint4& v1) {
          const uint4* src = reinterpret_cast<const uint4*>(x + (size_t)(blockIdx.x * 16 + r) * DM);
          v0 = __ldg(src + lane);
          v1 = __ldg(src + 32 + lane);
        };
        uint4 a0, a1, b0, b1;
        int r = warp - 1;
        ld(r, a0, a1);
        ld(r + 3, b0, b1);
        for (; r < 16; r += 3) {
          const uint32_t u[8] = {a0.x, a0.y, a0.z, a0.w, a1.x, a1.y, a1.z, a1.w};
          a0 = b0;
          a1 = b1;
          if (r + 6 < 16) ld(r + 6, b0, b1);
          float f[16];
          float s = 0.f;
#pragma unroll
          for (int i = 0; i < 8; i++) { f[2 * i] = bf_lo(u[i]); f[2 * i + 1] = bf_hi(u[i]); s += f[2 * i] + f[2 * i + 1]; }
#pragma unroll
          for (int o = 16; o > 0; o >>= 1) s += __shfl_xor_sync(0xffffffffu, s, o);
          const float mean = s * (1.f / DM);
          float q = 0.f;
#pragma unroll
          for (int i = 0; i < 16; i++) { f[i] -= mean; q += f[i] * f[i]; }
#pragma unroll
          for (int o = 16; o > 0; o >>= 1) q += __shfl_xor_sync(0xffffffffu, q, o);
          const float rstd = (0.08838834764831845f * 1.4426950408889634f) / sqrtf(q * (1.f / DM) + 1e-5f);
          uint4* dst = reinterpret_cast<uint4*>(g_xn + (size_t)(blockIdx.x * 16 + r) * DM);
          dst[lane] = make_uint4(pack_bf16(f[0] * rstd, f[1] * rstd), pack_bf16(f[2] * rstd, f[3] * rstd),
                                 pack_bf16(f[4] * rstd, f[5] * rstd), pack_bf16(f[6] * rstd, f[7] * rstd));
          dst[32 + lane] = make_uint4(pack_bf16(f[8] * rstd, f[9] * rstd), pack_bf16(f[10] * rstd, f[11] * rstd),
                                      pack_bf16(f[12] * rstd, f[13] * rstd), pack_bf16(f[14] * rstd, f[15] * rstd));
        }
      }
      __threadfence();
      __syncwarp();
      if (lane == 0) atomicAdd(g_ln_count + (blockIdx.x >> 3), 1u);
      const int task = blockIdx.x * 3 + (warp - 1);
      if (task < 352) {
        const int mat = task / 176, grp = task % 176;
        float a[8];
#pragma unroll
        for (int i = 0; i < 8; i++) a[i] = 0.f;
        if (grp < FF / 8) {
          const bf16* w = (mat ? w_up : w_gate) + grp * 8;
#pragma unroll 4
          for (int r = lane; r < DM; r += 32) {
            const uint4 v = __ldg(reinterpret_cast<const uint4*>(w + (size_t)r * FF));
            a[0] += bf_lo(v.x); a[1] += bf_hi(v.x); a[2] += bf_lo(v.y); a[3] += bf_hi(v.y);
            a[4] += bf_lo(v.z); a[5] += bf_hi(v.z); a[6] += bf_lo(v.w); a[7] += bf_hi(v.w);
          }
#pragma unroll
          for (int i = 0; i < 8; i++)
#pragma unroll
            for (int o = 16; o > 0; o >>= 1) a[i] += __shfl_xor_sync(0xffffffffu, a[i], o);
        }
        if (lane == 0) {
          float4* dst = reinterpret_cast<float4*>(g_cs + mat * 1408 + grp * 8);
          dst[0] = make_float4(a[0], a[1], a[2], a[3]);
          dst[1] = make_float4(a[4], a[5], a[6], a[7]);
        }
      }
    }
  } else {
    reg_inc<224>();
    const int cw = wg - 1;
    const int tid = threadIdx.x & 127;
    if (cw == 1) bar_arrive(1, 256);
    float acc[128];
    uint32_t pk[64];
    const size_t thr_off = (size_t)(mblk * 128 + cw * 64 + warp * 16 + (lane >> 2)) * HD + (lane & 3) * 8;
    bf16* prev_out = nullptr;
    auto store_piece = [&](int i) {
      bf16* dst = prev_out + (size_t)(i >> 2) * SEQ * HD + (i & 3) * 32;
      st_global_v4(dst, pk[8 * i], pk[8 * i + 2], pk[8 * i + 4], pk[8 * i + 6]);
      st_global_v4(dst + 8 * HD, pk[8 * i + 1], pk[8 * i + 3], pk[8 * i + 5], pk[8 * i + 7]);
    };
    for (int t = 0; t < 6; t++) {
#pragma unroll
      for (int k = 0; k < 8; k++) {
        const int st = k & 3;
        mbar_wait(bars + st * 8, (k >> 2) & 1);
        const uint32_t sa = base + st * KV_STAGE_BYTES;
        const uint32_t da = make_desc(sa + cw * 8192, 16);
        const uint32_t db = make_desc(sa + 16384, 8192);
        bar_sync(1 + cw, 256);
        wgmma_fence();
#pragma unroll
        for (int kk = 0; kk < 4; kk++) wgmma_ss_n256<1>(acc, desc_add(da, kk * 32), desc_add(db, kk * 2048), (k | kk) != 0);
        wgmma_commit();
        bar_arrive(2 - cw, 256);
        if (t > 0) store_piece(k);
        if (k > 0) {
          wgmma_wait<1>();
          if (tid == 0) mbar_arrive(bars + 64 + ((k - 1) & 3) * 8);
        }
      }
      wgmma_wait<0>();
      if (tid == 0) mbar_arrive(bars + 64 + 3 * 8);
      fence_regs(acc);
      const int mat = tile_matrix(t, ngrp);
#pragma unroll
      for (int i = 0; i < 64; i++) pk[i] = pack_bf16(acc[2 * i], acc[2 * i + 1]);
      prev_out = (mat == 0 ? g_k : mat == 1 ? g_v : g_q) + thr_off + (size_t)(tile_pair(t, ngrp) * 2) * SEQ * HD;
    }
#pragma unroll
    for (int i = 0; i < 8; i++) store_piece(i);
  }
}
constexpr int AT_SLOTS = 7;
constexpr int AT_SMEM = AT_SLOTS * 32768 + 1024 + 256;
struct AttnSched {
  int start[134];
  int tile[NH * 16];
};

struct RingPos {
  int slot;
  uint32_t phase;
  __device__ __forceinline__ void next() {
    if (++slot == AT_SLOTS) { slot = 0; phase ^= 1; }
  }
};

constexpr float SM_ZERO = 32.f;
constexpr float SM_LIMIT = 1099511627776.f;

template <int NG, bool SUB>
__device__ __forceinline__ void exp_pack(const float (&s)[64], uint32_t (&p)[32], float m0, float m1, float& r0, float& r1) {
  float a0 = 0.f, a1 = 0.f, b0 = 0.f, b1 = 0.f;
#pragma unroll
  for (int i = 0; i < NG; i++) {
    const float e0 = ex2(SUB ? s[4 * i] - m0 : s[4 * i]), e1 = ex2(SUB ? s[4 * i + 1] - m0 : s[4 * i + 1]);
    const float e2 = ex2(SUB ? s[4 * i + 2] - m1 : s[4 * i + 2]), e3 = ex2(SUB ? s[4 * i + 3] - m1 : s[4 * i + 3]);
    a0 += e0;
    b0 += e1;
    a1 += e2;
    b1 += e3;
    p[2 * i] = pack_bf16(e0, e1);
    p[2 * i + 1] = pack_bf16(e2, e3);
  }
#pragma unroll
  for (int i = 2 * NG; i < 32; i++) p[i] = 0u;
  r0 = a0 + b0;
  r1 = a1 + b1;
}

__device__ __forceinline__ void refresh_max(const float (&s)[64], float (&o)[64], float& m0, float& m1, float& l0, float& l1) {
  float a0 = fmaxf(s[0], s[1]), a1 = fmaxf(s[2], s[3]), b0 = fmaxf(s[4], s[5]), b1 = fmaxf(s[6], s[7]);
#pragma unroll
  for (int i = 2; i < 16; i += 2) {
    a0 = fmaxf(a0, fmaxf(s[4 * i], s[4 * i + 1]));
    a1 = fmaxf(a1, fmaxf(s[4 * i + 2], s[4 * i + 3]));
    b0 = fmaxf(b0, fmaxf(s[4 * i + 4], s[4 * i + 5]));
    b1 = fmaxf(b1, fmaxf(s[4 * i + 6], s[4 * i + 7]));
  }
  a0 = fmaxf(a0, b0);
  a1 = fmaxf(a1, b1);
  a0 = fmaxf(a0, __shfl_xor_sync(0xffffffffu, a0, 1));
  a1 = fmaxf(a1, __shfl_xor_sync(0xffffffffu, a1, 1));
  a0 = fmaxf(a0, __shfl_xor_sync(0xffffffffu, a0, 2));
  a1 = fmaxf(a1, __shfl_xor_sync(0xffffffffu, a1, 2));
  a0 = fmaxf(a0, m0);
  a1 = fmaxf(a1, m1);
  const float sc0 = ex2(m0 - a0), sc1 = ex2(m1 - a1);
  m0 = a0;
  m1 = a1;
  l0 *= sc0;
  l1 *= sc1;
#pragma unroll
  for (int i = 0; i < 16; i++) {
    o[4 * i] *= sc0;
    o[4 * i + 1] *= sc0;
    o[4 * i + 2] *= sc1;
    o[4 * i + 3] *= sc1;
  }
}

__device__ __forceinline__ void mask_diag(float (&s)[64], int cw, int warp, int lane) {
  const int t0 = cw * 64 + warp * 16 + (lane >> 2) - (lane & 3) * 2;
#pragma unroll
  for (int i = 0; i < 16; i++) {
    if (8 * i > t0) s[4 * i] = -INFINITY;
    if (8 * i + 1 > t0) s[4 * i + 1] = -INFINITY;
    if (8 * (i - 1) > t0) s[4 * i + 2] = -INFINITY;
    if (8 * (i - 1) + 1 > t0) s[4 * i + 3] = -INFINITY;
  }
}

__device__ __forceinline__ void load_q_frags(uint32_t (&q)[32], uint32_t sq, int cw, int warp, int lane) {
  const int row = cw * 64 + warp * 16 + (lane & 7) + ((lane >> 3) & 1) * 8;
  const uint32_t rbase = sq + row * 128;
#pragma unroll
  for (int j = 0; j < 8; j++) {
    const int chunk = (2 * j + (lane >> 4)) & 7;
    asm volatile("ldmatrix.sync.aligned.m8n8.x4.shared.b16 {%0, %1, %2, %3}, [%4];"
                 : "=r"(q[4 * j]), "=r"(q[4 * j + 1]), "=r"(q[4 * j + 2]), "=r"(q[4 * j + 3])
                 : "r"(rbase + (j >> 2) * 16384 + ((chunk ^ (row & 7)) << 4)) : "memory");
  }
}

__device__ __forceinline__ void row_recip(float l0, float l1, float& i0, float& i1) {
  l0 += __shfl_xor_sync(0xffffffffu, l0, 1);
  l1 += __shfl_xor_sync(0xffffffffu, l1, 1);
  l0 += __shfl_xor_sync(0xffffffffu, l0, 2);
  l1 += __shfl_xor_sync(0xffffffffu, l1, 2);
  asm("rcp.approx.ftz.f32 %0, %1;" : "=f"(i0) : "f"(l0));
  asm("rcp.approx.ftz.f32 %0, %1;" : "=f"(i1) : "f"(l1));
}
__device__ __forceinline__ void write_ctx(const float (&o)[64], float i0, float i1, bf16* dst) {
#pragma unroll
  for (int a = 0; a < 4; a++) {
    st_global_v4(dst + 32 * a, pack_bf16(o[16 * a] * i0, o[16 * a + 1] * i0), pack_bf16(o[16 * a + 4] * i0, o[16 * a + 5] * i0),
                 pack_bf16(o[16 * a + 8] * i0, o[16 * a + 9] * i0), pack_bf16(o[16 * a + 12] * i0, o[16 * a + 13] * i0));
    st_global_v4(dst + 32 * a + 8 * HD, pack_bf16(o[16 * a + 2] * i1, o[16 * a + 3] * i1), pack_bf16(o[16 * a + 6] * i1, o[16 * a + 7] * i1),
                 pack_bf16(o[16 * a + 10] * i1, o[16 * a + 11] * i1), pack_bf16(o[16 * a + 14] * i1, o[16 * a + 15] * i1));
  }
}

__global__ void __launch_bounds__(384, 1)
attn_kernel(const __grid_constant__ CUtensorMap mQ, const __grid_constant__ CUtensorMap mK, const __grid_constant__ CUtensorMap mV,
            const __grid_constant__ AttnSched sched) {
  extern __shared__ uint8_t smem_raw[];
  const uint32_t base = align1024(smem_u32(smem_raw));
  const uint32_t bar_full = base + AT_SLOTS * 32768, bar_empty = bar_full + 64;
  if (threadIdx.x == 0) {
    for (int i = 0; i < AT_SLOTS; i++) {
      mbar_init(bar_full + i * 8, 1);
      mbar_init(bar_empty + i * 8, 8);
    }
    asm volatile("fence.mbarrier_init.release.cluster;" ::: "memory");
  }
  if (threadIdx.x == 32) {
    tma_prefetch_desc(&mQ);
    tma_prefetch_desc(&mK);
    tma_prefetch_desc(&mV);
  }
  __syncthreads();
  pdl_launch();
  const int wg = threadIdx.x >> 7, warp = (threadIdx.x >> 5) & 3, lane = threadIdx.x & 31;
  const int t_begin = sched.start[blockIdx.x], t_end = sched.start[blockIdx.x + 1];
  if (wg == 0) {
    reg_dec<24>();
    if (warp == 0 && lane == 0) {
      RingPos rp{0, 1};
      auto load = [&](const CUtensorMap* m, int row) {
        mbar_wait(bar_empty + rp.slot * 8, rp.phase);
        const uint32_t dst = base + rp.slot * 32768, fb = bar_full + rp.slot * 8;
        mbar_expect_tx(fb, 32768);
        tma_load_2d(dst, m, 0, row, fb);
        tma_load_2d(dst + 16384, m, 64, row, fb);
        rp.next();
      };
      pdl_wait();
      int prev_v = -1;
      for (int ti = t_begin; ti < t_end; ti++) {
        const int tile = sched.tile[ti], h = tile >> 4, qb = tile & 15;
        if (ti == t_begin) load(&mQ, h * SEQ + qb * 128);
        for (int j = qb; j >= 0; j--) {
          if (prev_v >= 0) load(&mV, prev_v);
          prev_v = h * SEQ + (qb - j) * 128;
          load(&mK, prev_v);
          if (j == 0 && ti + 1 < t_end) {
            const int nt = sched.tile[ti + 1];
            load(&mQ, (nt >> 4) * SEQ + (nt & 15) * 128);
          }
        }
      }
      if (prev_v >= 0) load(&mV, prev_v);
    }
  } else {
    reg_inc<240>();
    const int cw = wg - 1;
    const int tid = threadIdx.x & 127;
    RingPos rp{0, 0};
    auto take = [&](int& slot) {
      mbar_wait(bar_full + rp.slot * 8, rp.phase);
      slot = rp.slot;
      rp.next();
    };
    auto release = [&](int slot) {
      if (lane == 0) mbar_arrive(bar_empty + slot * 8);
    };
    if (t_begin < t_end) {
      if (cw == 1) bar_arrive(1, 256);
      float s[64], o[64];
      uint32_t q[32], p[32];
      float m0, m1, l0 = 0.f, l1 = 0.f;
      auto ctx_ptr = [&](int t) {
        return g_ctx + (size_t)((t >> 4) * SEQ + (t & 15) * 128 + cw * 64 + warp * 16 + (lane >> 2)) * HD + (lane & 3) * 8;
      };
      int slot_q = 0, slot_v = 0, slot_k = 0;
      auto issue_pv = [&](bool accumulate) {
        const uint32_t dv = make_desc(base + slot_v * 32768, 16384);
#pragma unroll
        for (int kk = 0; kk < 8; kk++)
          wgmma_rs_n128<1>(o, p[4 * kk], p[4 * kk + 1], p[4 * kk + 2], p[4 * kk + 3], desc_add(dv, kk * 2048), kk != 0 || accumulate);
      };
      auto issue_qk = [&]() {
        const uint32_t dk = make_desc(base + slot_k * 32768, 16);
#pragma unroll
        for (int kk = 0; kk < 8; kk++)
          wgmma_rs_n128<0>(s, q[4 * kk], q[4 * kk + 1], q[4 * kk + 2], q[4 * kk + 3],
                           desc_add(dk, (kk >> 2) * 16384 + (kk & 3) * 32), kk != 0);
      };
      auto take_next = [&](bool last_block, bool more_tiles) {
        if (last_block && more_tiles) take(slot_q);
        take(slot_v);
        if (!last_block || more_tiles) take(slot_k);
      };

      auto start_tile = [&]() {
        const float a0 = __shfl_sync(0xffffffffu, s[0], lane & 28), a1 = __shfl_sync(0xffffffffu, s[2], lane & 28);
        m0 = fabsf(a0) <= SM_ZERO ? 0.f : a0;
        m1 = fabsf(a1) <= SM_ZERO ? 0.f : a1;
        l0 = 0.f;
        l1 = 0.f;
      };

      int ti = t_begin;
      int j = sched.tile[ti] & 15;
      take(slot_q);
      load_q_frags(q, base + slot_q * 32768, cw, warp, lane);
      release(slot_q);
      take(slot_k);
      bar_sync(1 + cw, 256);
      wgmma_fence();
      issue_qk();
      wgmma_commit();
      bar_arrive(2 - cw, 256);
      int done_k = slot_k;
      bool more = ti + 1 < t_end;
      take_next(j == 0, more);
#pragma unroll
      for (int i = 0; i < 64; i++) o[i] = 0.f;
      wgmma_wait<0>();
      release(done_k);
      fence_regs(s);
      start_tile();
      if (j == 0) mask_diag(s, cw, warp, lane);
      bool fresh = true;
#pragma unroll 1
      while (true) {
        float r0, r1;
        bool general = !__all_sync(0xffffffffu, m0 == 0.f && m1 == 0.f), refresh = false;
        if (!general) {
          exp_pack<16, false>(s, p, m0, m1, r0, r1);
          general = refresh = __any_sync(0xffffffffu, !(r0 <= SM_LIMIT && r1 <= SM_LIMIT));
        }
        if (general) {
#pragma unroll 1
          while (true) {
            if (refresh) refresh_max(s, o, m0, m1, l0, l1);
            exp_pack<16, true>(s, p, m0, m1, r0, r1);
            if (refresh || !__any_sync(0xffffffffu, !(r0 <= SM_LIMIT && r1 <= SM_LIMIT))) break;
            refresh = true;
          }
        }
        l0 += r0;
        l1 += r1;
        if (j == 0) {
          if (!more) break;
          load_q_frags(q, base + slot_q * 32768, cw, warp, lane);
          release(slot_q);
        }
        bar_sync(1 + cw, 256);
        wgmma_fence();
        issue_pv(!fresh);
        issue_qk();
        wgmma_commit();
        bar_arrive(2 - cw, 256);
        const int done_v = slot_v;
        done_k = slot_k;
        fresh = j == 0;
        if (fresh) {
          j = sched.tile[++ti] & 15;
          more = ti + 1 < t_end;
        } else {
          j--;
        }
        take_next(j == 0, more);
        float i0, i1;
        if (fresh) row_recip(l0, l1, i0, i1);
        wgmma_wait<0>();
        release(done_v);
        release(done_k);
        fence_regs(s);
        fence_regs(o);
        if (fresh) {
          write_ctx(o, i0, i1, ctx_ptr(sched.tile[ti - 1]));
          start_tile();
        }
        if (j == 0) mask_diag(s, cw, warp, lane);
      }
      bar_sync(1 + cw, 256);
      wgmma_fence();
      issue_pv(!fresh);
      wgmma_commit();
      bar_arrive(2 - cw, 256);
      float i0, i1;
      row_recip(l0, l1, i0, i1);
      wgmma_wait<0>();
      fence_regs(o);
      write_ctx(o, i0, i1, ctx_ptr(sched.tile[t_end - 1]));
    }
  }
}
constexpr int TL_XBUF = 196608;
constexpr int TL_CS = TL_XBUF + 32768;
constexpr int TL_BARS = TL_CS + 1408;
constexpr int TL_SMEM = TL_BARS + 192 + 1024;
constexpr int ACT_PITCH = 1408;

__device__ __forceinline__ void tma_load_5d(uint32_t dst, const CUtensorMap* map, int c0, int c4, uint32_t bar) {
  asm volatile("cp.async.bulk.tensor.5d.shared::cluster.global.mbarrier::complete_tx::bytes [%0], [%1, {%3, %4, %4, %4, %5}], [%2];"
               ::"r"(dst), "l"(map), "r"(bar), "r"(c0), "r"(0), "r"(c4) : "memory");
}
__device__ __forceinline__ uint32_t relu_mul_bf16x2(uint32_t g, uint32_t u) {
  uint32_t r;
  asm("{\n.reg .b32 t;\nmax.NaN.bf16x2 t, %1, %3;\nmul.rn.bf16x2 %0, t, %2;\n}" : "=r"(r) : "r"(g), "r"(u), "r"(0u));
  return r;
}
__device__ __forceinline__ void team_arrive(unsigned int* ctr) {
  asm volatile("fence.acq_rel.gpu;\nred.relaxed.gpu.global.add.u32 [%0], 1;" ::"l"(ctr) : "memory");
}
__device__ __forceinline__ void st_global_v2(void* p, uint32_t a, uint32_t b) {
  asm volatile("st.global.v2.b32 [%0], {%1, %2};" ::"l"(p), "r"(a), "r"(b));
}

template <int NSTEPS>
__device__ __forceinline__ void gemm_split_k(float (&acc)[64], uint32_t base, uint32_t bar_full, int cw, int tid) {
  const uint32_t bar_empty = bar_full + 32;
#pragma unroll 1
  for (int s = 0; s < NSTEPS; s++) {
    const int st = s & 3;
    mbar_wait(bar_full + st * 8, (s >> 2) & 1);
    const uint32_t sa = base + st * 49152;
    const uint32_t da = make_desc(sa + cw * 8192, 16);
    const uint32_t db = make_desc(sa + 16384 + cw * 8192, 16384);
    wgmma_fence();
#pragma unroll
    for (int i = 0; i < 4; i++) wgmma_ss_n128<1>(acc, desc_add(da, i * 32), desc_add(db, i * 2048), (s | i) != 0);
    wgmma_commit();
    if (s > 0) {
      wgmma_wait<1>();
      if (tid == 0) mbar_arrive(bar_empty + ((s - 1) & 3) * 8);
    }
  }
  wgmma_wait<0>();
  if (tid == 0) mbar_arrive(bar_empty + ((NSTEPS - 1) & 3) * 8);
  fence_regs(acc);
}

template <int CW>
__device__ __forceinline__ void reduce_add_residual_t(const float (&acc)[64], const uint32_t (&res)[16], uint32_t (&pk)[16], uint32_t xbuf,
                                                      int tid) {
  constexpr int SEND = CW ? 0 : 32, KEEP = CW ? 32 : 0;
  const uint32_t wr = xbuf + CW * 16384 + tid * 16, rd = xbuf + (CW ^ 1) * 16384 + tid * 16;
#pragma unroll
  for (int i = 0; i < 8; i++)
    asm volatile("st.shared.v4.f32 [%0], {%1, %2, %3, %4};" ::"r"(wr + i * 2048), "f"(acc[SEND + 4 * i]), "f"(acc[SEND + 4 * i + 1]),
                 "f"(acc[SEND + 4 * i + 2]), "f"(acc[SEND + 4 * i + 3]) : "memory");
  bar_sync(1, 256);
#pragma unroll
  for (int i = 0; i < 8; i++) {
    float4 t;
    asm volatile("ld.shared.v4.f32 {%0, %1, %2, %3}, [%4];" : "=f"(t.x), "=f"(t.y), "=f"(t.z), "=f"(t.w) : "r"(rd + i * 2048) : "memory");
    const uint32_t p0 = pack_bf16(t.x + acc[KEEP + 4 * i], t.y + acc[KEEP + 4 * i + 1]);
    const uint32_t p1 = pack_bf16(t.z + acc[KEEP + 4 * i + 2], t.w + acc[KEEP + 4 * i + 3]);
    pk[2 * i] = pack_bf16(bf_lo(p0) + bf_lo(res[2 * i]), bf_hi(p0) + bf_hi(res[2 * i]));
    pk[2 * i + 1] = pack_bf16(bf_lo(p1) + bf_lo(res[2 * i + 1]), bf_hi(p1) + bf_hi(res[2 * i + 1]));
  }
}
__device__ __forceinline__ void reduce_add_residual(const float (&acc)[64], const uint32_t (&res)[16], uint32_t (&pk)[16], uint32_t xbuf,
                                                    int cw, int tid) {
  if (cw == 0) reduce_add_residual_t<0>(acc, res, pk, xbuf, tid);
  else reduce_add_residual_t<1>(acc, res, pk, xbuf, tid);
}

__global__ void __launch_bounds__(384, 1)
tail_kernel(const __grid_constant__ CUtensorMap mCtx, const __grid_constant__ CUtensorMap mWo, const __grid_constant__ CUtensorMap mH,
            const __grid_constant__ CUtensorMap mWg, const __grid_constant__ CUtensorMap mWu, const __grid_constant__ CUtensorMap mAct,
            const __grid_constant__ CUtensorMap mWd, const __grid_constant__ CUtensorMap mOut, const bf16* __restrict__ x) {
  extern __shared__ uint8_t smem_raw[];
  const uint32_t base = align1024(smem_u32(smem_raw));
  const uint32_t barC = base + TL_BARS, barD = barC + 64, barE = barD + 64;
  if (threadIdx.x == 0) {
    for (int i = 0; i < 12; i++) {
      mbar_init(barC + (i >> 2) * 64 + (i & 3) * 8, 1);
      mbar_init(barC + (i >> 2) * 64 + 32 + (i & 3) * 8, 2);
    }
    asm volatile("fence.mbarrier_init.release.cluster;" ::: "memory");
  }
  if (threadIdx.x == 32) {
    tma_prefetch_desc(&mWo);
    tma_prefetch_desc(&mCtx);
    tma_prefetch_desc(&mWg);
    tma_prefetch_desc(&mWu);
    tma_prefetch_desc(&mH);
    tma_prefetch_desc(&mWd);
    tma_prefetch_desc(&mAct);
    tma_prefetch_desc(&mOut);
  }
  __syncthreads();
  const int team = blockIdx.x >> 3, member = blockIdx.x & 7;
  const int mhalf = member >> 2, nt = member & 3;
  const int m64 = team * 2 + mhalf;
  const int n0 = member * 176;
  const int wg = threadIdx.x >> 7, warp = (threadIdx.x >> 5) & 3, lane = threadIdx.x & 31;
  if (wg == 0) {
    reg_dec<40>();
    if (warp == 0 && lane == 0) {
      auto load_wo = [&](int s) {
        const uint32_t dst = base + (s & 3) * 49152, fb = barC + (s & 3) * 8;
        mbar_expect_tx(fb, 49152);
        tma_load_2d(dst + 16384, &mWo, nt * 128, s * 128, fb);
        tma_load_2d(dst + 32768, &mWo, nt * 128 + 64, s * 128, fb);
      };
      for (int s = 0; s < 4; s++) load_wo(s);
      pdl_wait();
      for (int s = 0; s < NH; s++) {
        const uint32_t dst = base + (s & 3) * 49152, fb = barC + (s & 3) * 8;
        if (s >= 4) {
          mbar_wait(barC + 32 + (s & 3) * 8, ((s >> 2) & 1) ^ 1);
          load_wo(s);
        }
        tma_load_2d(dst, &mCtx, 0, s * SEQ + m64 * 64, fb);
        tma_load_2d(dst + 8192, &mCtx, 64, s * SEQ + m64 * 64, fb);
      }
      for (int it = 0; it < 8; it++) {
        const int st = it % 3;
        if (it < 3) {
          if (it == 0) mbar_wait(barC + 32, 1);
          mbar_wait(barC + 32 + (it + 1) * 8, 1);
        } else {
          mbar_wait(barD + 32 + st * 8, ((it / 3) & 1) ^ 1);
        }
        const uint32_t dst = base + st * 65536, fb = barD + st * 8;
        mbar_expect_tx(fb, 65536);
#pragma unroll
        for (int c = 0; c < 3; c++) {
          tma_load_5d(dst + 16384 + c * 8192, &mWg, n0 + c * 64, it * 2, fb);
          tma_load_5d(dst + 40960 + c * 8192, &mWu, n0 + c * 64, it * 2, fb);
        }
        if (it == 2) {
          spin_until(g_team + team * 4, 16);
          asm volatile("fence.proxy.async.global;" ::: "memory");
          tma_load_2d(base, &mH, 0, team * 128, barD);
          tma_load_2d(base + 65536, &mH, 64, team * 128, barD + 8);
        }
        if (it >= 2) tma_load_2d(dst, &mH, it * 64, team * 128, fb);
      }
      for (int s = 0; s < 11; s++) {
        const int st = s & 3;
        if (s < 4) {
          if (s == 0) mbar_wait(barD + 32, 0);
          if (s == 1) mbar_wait(barD + 32 + 8, 0);
          if (s == 2) mbar_wait(barD + 32 + 16, 1);
        } else {
          mbar_wait(barE + 32 + st * 8, ((s >> 2) & 1) ^ 1);
        }
        const uint32_t dst = base + st * 49152, fb = barE + st * 8;
        mbar_expect_tx(fb, 49152);
        tma_load_5d(dst + 16384, &mWd, nt * 128, s * 8, fb);
        tma_load_5d(dst + 32768, &mWd, nt * 128 + 64, s * 8, fb);
        if (s == 3) {
          spin_until(g_team + team * 4 + 1, 16);
          asm volatile("fence.proxy.async.global;" ::: "memory");
          for (int i = 0; i < 3; i++) {
            tma_load_2d(base + i * 49152, &mAct, i * 128, m64 * 64, barE + i * 8);
            tma_load_2d(base + i * 49152 + 8192, &mAct, i * 128 + 64, m64 * 64, barE + i * 8);
          }
        }
        if (s >= 3) {
          tma_load_2d(dst, &mAct, s * 128, m64 * 64, fb);
          tma_load_2d(dst + 8192, &mAct, s * 128 + 64, m64 * 64, fb);
        }
      }
    } else if (warp == 1) {
      pdl_wait();
      if (blockIdx.x == 0 && lane < 16) g_ln_count[lane] = 0;
      for (int i = lane; i < 352; i += 32) {
        const float c = __ldcg(g_cs + (i / 176) * 1408 + n0 + (i % 176));
        asm volatile("st.shared.f32 [%0], %1;" ::"r"(base + TL_CS + i * 4), "f"(c) : "memory");
      }
      bar_arrive(4, 288);
    }
  } else {
    reg_inc<232>();
    const int cw = wg - 1;
    const int tid = threadIdx.x & 127;
    const uint32_t xbuf = base + TL_XBUF;
    uint32_t hk[16];
    const int row0 = m64 * 64 + warp * 16 + (lane >> 2);
    {
      const int col0 = nt * 128 + cw * 64 + (lane & 3) * 2;
      uint32_t res[16];
#pragma unroll
      for (int i = 0; i < 8; i++) {
        res[2 * i] = __ldg(reinterpret_cast<const uint32_t*>(x + (size_t)row0 * DM + col0 + 8 * i));
        res[2 * i + 1] = __ldg(reinterpret_cast<const uint32_t*>(x + (size_t)(row0 + 8) * DM + col0 + 8 * i));
      }
      float acc[64];
      gemm_split_k<NH>(acc, base, barC, cw, tid);
      reduce_add_residual(acc, res, hk, xbuf, cw, tid);
      bf16* const hp = g_h + (size_t)row0 * DM + nt * 128 + cw * 64 + (lane & 3) * 8;
#pragma unroll
      for (int a = 0; a < 2; a++) {
        st_global_v4(hp + 32 * a, hk[8 * a], hk[8 * a + 2], hk[8 * a + 4], hk[8 * a + 6]);
        st_global_v4(hp + 32 * a + 8 * DM, hk[8 * a + 1], hk[8 * a + 3], hk[8 * a + 5], hk[8 * a + 7]);
      }
      bar_sync(2 + cw, 128);
      if (tid == 0) team_arrive(g_team + team * 4);
      float s0 = 0.f, s1 = 0.f;
#pragma unroll
      for (int i = 0; i < 8; i++) {
        s0 += bf_lo(hk[2 * i]) + bf_hi(hk[2 * i]);
        s1 += bf_lo(hk[2 * i + 1]) + bf_hi(hk[2 * i + 1]);
      }
      s0 += __shfl_xor_sync(0xffffffffu, s0, 1); s1 += __shfl_xor_sync(0xffffffffu, s1, 1);
      s0 += __shfl_xor_sync(0xffffffffu, s0, 2); s1 += __shfl_xor_sync(0xffffffffu, s1, 2);
      const float mu0 = s0 * (1.f / 64), mu1 = s1 * (1.f / 64);
      float q0 = 0.f, q1 = 0.f;
#pragma unroll
      for (int i = 0; i < 8; i++) {
        const float a = bf_lo(hk[2 * i]) - mu0, b = bf_hi(hk[2 * i]) - mu0, c = bf_lo(hk[2 * i + 1]) - mu1, d = bf_hi(hk[2 * i + 1]) - mu1;
        q0 += a * a + b * b;
        q1 += c * c + d * d;
      }
      q0 += __shfl_xor_sync(0xffffffffu, q0, 1); q1 += __shfl_xor_sync(0xffffffffu, q1, 1);
      q0 += __shfl_xor_sync(0xffffffffu, q0, 2); q1 += __shfl_xor_sync(0xffffffffu, q1, 2);
      if ((lane & 3) == 0) {
        g_stats[row0 * 8 + nt * 2 + cw] = make_float2(mu0, q0);
        g_stats[(row0 + 8) * 8 + nt * 2 + cw] = make_float2(mu1, q1);
      }
      bar_sync(2 + cw, 128);
      if (tid == 0) team_arrive(g_team + team * 4 + 2);
    }
    {
      float ag[88], au[88];
      float mean[2], rstd[2];
      int st = 0, prev = 0;
      uint32_t ph = 0;
#pragma unroll 1
      for (int it = 0; it < 8; it++) {
        mbar_wait(barD + st * 8, ph);
        const uint32_t sa = base + st * 65536;
        const uint32_t da = make_desc(sa + cw * 8192, 16);
        const uint32_t dg = make_desc(sa + 16384, 8192);
        const uint32_t du = make_desc(sa + 40960, 8192);
        wgmma_fence();
#pragma unroll
        for (int kk = 0; kk < 4; kk++) {
          wgmma_ss_n176<1>(ag, desc_add(da, kk * 32), desc_add(dg, kk * 2048), (it | kk) != 0);
          wgmma_ss_n176<1>(au, desc_add(da, kk * 32), desc_add(du, kk * 2048), (it | kk) != 0);
        }
        wgmma_commit();
        if (it > 0) {
          wgmma_wait<1>();
          if (tid == 0) mbar_arrive(barD + 32 + prev * 8);
        }
        prev = st;
        if (++st == 3) { st = 0; ph ^= 1; }
      }
      if (tid == 0) spin_until(g_team + team * 4 + 2, 16);
      bar_sync(2 + cw, 128);
      const int drow = team * 128 + cw * 64 + warp * 16 + (lane >> 2);
#pragma unroll
      for (int r = 0; r < 2; r++) {
        const float4* sp = reinterpret_cast<const float4*>(g_stats + (drow + 8 * r) * 8);
        const float4 a = __ldcg(sp), b = __ldcg(sp + 1), c = __ldcg(sp + 2), d = __ldcg(sp + 3);
        const float mu = (a.x + a.z + b.x + b.z + c.x + c.z + d.x + d.z) * 0.125f;
        float m2 = a.y + a.w + b.y + b.w + c.y + c.w + d.y + d.w;
        m2 += 64.f * ((a.x - mu) * (a.x - mu) + (a.z - mu) * (a.z - mu) + (b.x - mu) * (b.x - mu) + (b.z - mu) * (b.z - mu) +
                      (c.x - mu) * (c.x - mu) + (c.z - mu) * (c.z - mu) + (d.x - mu) * (d.x - mu) + (d.z - mu) * (d.z - mu));
        mean[r] = mu;
        rstd[r] = 1.f / sqrtf(m2 * (1.f / DM) + 1e-5f);
      }
      bar_sync(4, 288);
      wgmma_wait<0>();
      if (tid == 0) mbar_arrive(barD + 32 + prev * 8);
      fence_regs(ag);
      fence_regs(au);
      bf16* const actp = g_act + (size_t)drow * ACT_PITCH + n0 + (lane & 3) * 4;
      uint32_t csb = base + TL_CS + (lane & 3) * 8;
      asm volatile("" : "+r"(csb)::"memory");
#pragma unroll
      for (int j = 0; j < 11; j++) {
        uint32_t o4[4];
#pragma unroll
        for (int hh = 0; hh < 2; hh++) {
          const int i = 2 * j + hh;
          float2 cg, cu;
          asm("ld.shared.v2.f32 {%0, %1}, [%2];" : "=f"(cg.x), "=f"(cg.y) : "r"(csb + i * 32));
          asm("ld.shared.v2.f32 {%0, %1}, [%2];" : "=f"(cu.x), "=f"(cu.y) : "r"(csb + 704 + i * 32));
#pragma unroll
          for (int r = 0; r < 2; r++) {
            const uint32_t g = pack_bf16(fmaf(-mean[r], cg.x, ag[4 * i + 2 * r]) * rstd[r], fmaf(-mean[r], cg.y, ag[4 * i + 2 * r + 1]) * rstd[r]);
            const uint32_t u = pack_bf16(fmaf(-mean[r], cu.x, au[4 * i + 2 * r]) * rstd[r], fmaf(-mean[r], cu.y, au[4 * i + 2 * r + 1]) * rstd[r]);
            o4[2 * hh + r] = relu_mul_bf16x2(g, u);
          }
        }
        st_global_v2(actp + j * 16, o4[0], o4[2]);
        st_global_v2(actp + j * 16 + 8 * ACT_PITCH, o4[1], o4[3]);
      }
      bar_sync(2 + cw, 128);
      if (tid == 0) team_arrive(g_team + team * 4 + 1);
    }
    {
      float acc[64];
      gemm_split_k<11>(acc, base, barE, cw, tid);
      uint32_t pk[16];
      reduce_add_residual(acc, hk, pk, xbuf, cw, tid);
      const uint32_t mystag = xbuf + (cw ^ 1) * 16384;
      bar_sync(2 + cw, 128);
      const int row = warp * 16 + (lane & 7) + ((lane >> 3) & 1) * 8;
#pragma unroll
      for (int j = 0; j < 4; j++) {
        const int chunk = 2 * j + (lane >> 4);
        stmatrix_x4(mystag + row * 128 + ((chunk ^ (row & 7)) << 4), pk[4 * j], pk[4 * j + 1], pk[4 * j + 2], pk[4 * j + 3]);
      }
      fence_async_smem();
      bar_sync(2 + cw, 128);
      if (tid == 0) {
        tma_store_2d(&mOut, mystag, nt * 128 + cw * 64, m64 * 64);
        bulk_commit();
        bulk_wait_read<0>();
      }
    }
  }
}
typedef CUresult (*EncodeTiledFn)(CUtensorMap*, CUtensorMapDataType, cuuint32_t, void*, const cuuint64_t*, const cuuint64_t*,
                                  const cuuint32_t*, const cuuint32_t*, CUtensorMapInterleave, CUtensorMapSwizzle,
                                  CUtensorMapL2promotion, CUtensorMapFloatOOBfill);

EncodeTiledFn encode_fn() {
  static EncodeTiledFn fn = nullptr;
  if (!fn) {
    void* p = nullptr;
    cudaDriverEntryPointQueryResult q;
    cudaGetDriverEntryPoint("cuTensorMapEncodeTiled", &p, cudaEnableDefault, &q);
    fn = (EncodeTiledFn)p;
  }
  return fn;
}

CUtensorMap map2d(const void* ptr, uint64_t inner, uint64_t outer, uint64_t pitch_elems, uint32_t box_inner, uint32_t box_outer,
                  CUtensorMapSwizzle sw = CU_TENSOR_MAP_SWIZZLE_128B) {
  CUtensorMap m;
  cuuint64_t dims[2] = {inner, outer};
  cuuint64_t strides[1] = {pitch_elems * 2};
  cuuint32_t box[2] = {box_inner, box_outer};
  cuuint32_t es[2] = {1, 1};
  encode_fn()(&m, CU_TENSOR_MAP_DATA_TYPE_BFLOAT16, 2, const_cast<void*>(ptr), dims, strides, box, es, CU_TENSOR_MAP_INTERLEAVE_NONE, sw,
              CU_TENSOR_MAP_L2_PROMOTION_L2_256B, CU_TENSOR_MAP_FLOAT_OOB_FILL_NONE);
  return m;
}

CUtensorMap map3d_chunks(const void* ptr, uint64_t rows, uint64_t cols, uint32_t box_rows, uint32_t chunks) {
  CUtensorMap m;
  cuuint64_t dims[3] = {64, rows, cols / 64};
  cuuint64_t strides[2] = {cols * 2, 128};
  cuuint32_t box[3] = {64, box_rows, chunks};
  cuuint32_t es[3] = {1, 1, 1};
  encode_fn()(&m, CU_TENSOR_MAP_DATA_TYPE_BFLOAT16, 3, const_cast<void*>(ptr), dims, strides, box, es, CU_TENSOR_MAP_INTERLEAVE_NONE,
              CU_TENSOR_MAP_SWIZZLE_128B, CU_TENSOR_MAP_L2_PROMOTION_L2_256B, CU_TENSOR_MAP_FLOAT_OOB_FILL_NONE);
  return m;
}

CUtensorMap map5d_perm32(const void* ptr, uint64_t rows, uint64_t cols, uint32_t groups) {
  CUtensorMap m;
  const cuuint64_t row = cols * 2;
  cuuint64_t dims[5] = {cols, 2, 4, 4, rows / 32};
  cuuint64_t strides[4] = {row, 8 * row, 2 * row, 32 * row};
  cuuint32_t box[5] = {64, 2, 4, 4, groups};
  cuuint32_t es[5] = {1, 1, 1, 1, 1};
  encode_fn()(&m, CU_TENSOR_MAP_DATA_TYPE_BFLOAT16, 5, const_cast<void*>(ptr), dims, strides, box, es, CU_TENSOR_MAP_INTERLEAVE_NONE,
              CU_TENSOR_MAP_SWIZZLE_128B, CU_TENSOR_MAP_L2_PROMOTION_L2_256B, CU_TENSOR_MAP_FLOAT_OOB_FILL_NONE);
  return m;
}
CUtensorMap map5d_perm16(const void* ptr, uint64_t rows, uint64_t cols, uint32_t groups) {
  CUtensorMap m;
  const cuuint64_t row = cols * 2;
  cuuint64_t dims[5] = {cols, 2, 2, 4, rows / 16};
  cuuint64_t strides[4] = {row, 8 * row, 2 * row, 16 * row};
  cuuint32_t box[5] = {64, 2, 2, 4, groups};
  cuuint32_t es[5] = {1, 1, 1, 1, 1};
  encode_fn()(&m, CU_TENSOR_MAP_DATA_TYPE_BFLOAT16, 5, const_cast<void*>(ptr), dims, strides, box, es, CU_TENSOR_MAP_INTERLEAVE_NONE,
              CU_TENSOR_MAP_SWIZZLE_128B, CU_TENSOR_MAP_L2_PROMOTION_L2_256B, CU_TENSOR_MAP_FLOAT_OOB_FILL_NONE);
  return m;
}

template <typename T> void* sym_addr(T& sym) {
  void* p = nullptr;
  cudaGetSymbolAddress(&p, sym);
  return p;
}

void build_schedule(AttnSched& s, int ncta) {
  static int lists[134][64];
  int cnt[134] = {0};
  float load[134] = {0};
  auto cost = [](int tile) { return (float)((tile & 15) + 1) + 0.65f; };
  constexpr int GROUP = 8;
  for (int g = 0; g < NH / GROUP; g++)
    for (int qb = 15; qb >= 0; qb--)
      for (int h = g * GROUP; h < (g + 1) * GROUP; h++) {
        int best = 0;
        for (int c = 1; c < ncta; c++)
          if (load[c] < load[best]) best = c;
        lists[best][cnt[best]++] = h * 16 + qb;
        load[best] += cost(h * 16 + qb);
      }
  for (int iter = 0; iter < 4000; iter++) {
    int hi = 0;
    for (int c = 1; c < ncta; c++)
      if (load[c] > load[hi]) hi = c;
    float best_max = load[hi] - 1e-3f;
    int bi = -1, bc = -1, bj = -1;
    for (int c = 0; c < ncta; c++) {
      if (c == hi) continue;
      for (int i = 0; i < cnt[hi]; i++) {
        const float ci = cost(lists[hi][i]);
        for (int j = 0; j < cnt[c]; j++) {
          if (lists[c][j] / (16 * GROUP) != lists[hi][i] / (16 * GROUP)) continue;
          const float cj = cost(lists[c][j]);
          const float m = fmaxf(load[hi] - ci + cj, load[c] - cj + ci);
          if (m < best_max) { best_max = m; bi = i; bc = c; bj = j; }
        }
      }
    }
    if (bi < 0) break;
    const int ti = lists[hi][bi], tj = lists[bc][bj];
    lists[hi][bi] = tj;
    lists[bc][bj] = ti;
    load[hi] += cost(tj) - cost(ti);
    load[bc] += cost(ti) - cost(tj);
  }
  int pos = 0;
  for (int c = 0; c < ncta; c++) {
    s.start[c] = pos;
    for (int i = 0; i < cnt[c]; i++) s.tile[pos++] = lists[c][i];
  }
  for (int c = ncta; c < 134; c++) s.start[c] = pos;
}

template <typename... KArgs, typename... Args>
void launch(void (*kern)(KArgs...), int grid, int smem, bool pdl, Args... args) {
  cudaLaunchConfig_t cfg = {};
  cfg.gridDim = dim3(grid);
  cfg.blockDim = dim3(384);
  cfg.dynamicSmemBytes = smem;
  cfg.stream = cudaStreamPerThread;
  cudaLaunchAttribute at[1];
  at[0].id = cudaLaunchAttributeProgrammaticStreamSerialization;
  at[0].val.programmaticStreamSerializationAllowed = 1;
  cfg.attrs = at;
  cfg.numAttrs = pdl ? 1 : 0;
  cudaLaunchKernelEx(&cfg, kern, KArgs(args)...);
}

}

extern "C" void kernel_launch(void* const* d_in, const int* in_sizes, int n_in, void* d_out, int out_size) {
  const bf16* x = (const bf16*)d_in[0];
  const bf16* ckv = (const bf16*)d_in[1];
  const bf16* wq = (const bf16*)d_in[2];
  const bf16* wuk = (const bf16*)d_in[3];
  const bf16* wuv = (const bf16*)d_in[4];
  const bf16* wo = (const bf16*)d_in[5];
  const bf16* wgate = (const bf16*)d_in[7];
  const bf16* wup = (const bf16*)d_in[8];
  const bf16* wdown = (const bf16*)d_in[9];
  bf16* out = (bf16*)d_out;

  static bool init = false;
  static AttnSched sched;
  static int nsm = 132;
  static void *p_xn, *p_q, *p_k, *p_v, *p_ctx, *p_h, *p_act;
  if (!init) {
    cudaFuncSetAttribute(qkv_kernel, cudaFuncAttributeMaxDynamicSharedMemorySize, KV_SMEM);
    cudaFuncSetAttribute(attn_kernel, cudaFuncAttributeMaxDynamicSharedMemorySize, AT_SMEM);
    cudaFuncSetAttribute(tail_kernel, cudaFuncAttributeMaxDynamicSharedMemorySize, TL_SMEM);
    int dev = 0;
    cudaGetDevice(&dev);
    cudaDeviceGetAttribute(&nsm, cudaDevAttrMultiProcessorCount, dev);
    if (nsm > 132) nsm = 132;
    build_schedule(sched, nsm);
    p_xn = sym_addr(g_xn); p_q = sym_addr(g_q); p_k = sym_addr(g_k); p_v = sym_addr(g_v); p_ctx = sym_addr(g_ctx); p_h = sym_addr(g_h); p_act = sym_addr(g_act);
    init = true;
  }

  const CUtensorMap mCkv = map2d(ckv, DM, SEQ, DM, 64, 128);
  const CUtensorMap mXn = map2d(p_xn, DM, SEQ, DM, 64, 128);
  const CUtensorMap mWk = map3d_chunks(wuk, DM, NH * HD, 64, 4);
  const CUtensorMap mWv = map3d_chunks(wuv, DM, NH * HD, 64, 4);
  const CUtensorMap mWq = map3d_chunks(wq, DM, NH * HD, 64, 4);
  launch(qkv_kernel, 128, KV_SMEM, false, mCkv, mXn, mWk, mWv, mWq, x, wgate, wup);

  const CUtensorMap mQ = map2d(p_q, HD, NH * SEQ, HD, 64, 128);
  const CUtensorMap mK = map2d(p_k, HD, NH * SEQ, HD, 64, 128);
  const CUtensorMap mV = map2d(p_v, HD, NH * SEQ, HD, 64, 128);
  launch(attn_kernel, nsm, AT_SMEM, true, mQ, mK, mV, sched);

  const CUtensorMap mCtx = map2d(p_ctx, HD, NH * SEQ, HD, 64, 64);
  const CUtensorMap mWo = map2d(wo, DM, NH * HD, DM, 64, 128);
  const CUtensorMap mH = map2d(p_h, DM, SEQ, DM, 64, 128);
  const CUtensorMap mWg = map5d_perm32(wgate, DM, FF, 2);
  const CUtensorMap mWu = map5d_perm32(wup, DM, FF, 2);
  const CUtensorMap mAct = map2d(p_act, ACT_PITCH, SEQ, ACT_PITCH, 64, 64);
  const CUtensorMap mWd = map5d_perm16(wdown, FF, DM, 8);
  const CUtensorMap mOut = map2d(out, DM, SEQ, DM, 64, 64);
  launch(tail_kernel, 128, TL_SMEM, true, mCtx, mWo, mH, mWg, mWu, mAct, mWd, mOut, x);
}
```

```cpp
#include <cuda_runtime.h>
#include <cuda_bf16.h>
#include <cuda.h>
#include <stdint.h>

#pragma nv_diag_suppress 549

namespace {

constexpr int SEQ = 2048, DM = 512, NH = 32, HD = 128, FF = 1376;
typedef __nv_bfloat16 bf16;

__device__ __align__(1024) bf16 g_xn[SEQ * DM];
__device__ __align__(1024) bf16 g_q[NH * SEQ * HD];
__device__ __align__(1024) bf16 g_k[NH * SEQ * HD];
__device__ __align__(1024) bf16 g_v[NH * SEQ * HD];
__device__ __align__(1024) bf16 g_ctx[NH * SEQ * HD];
__device__ __align__(1024) bf16 g_h[SEQ * DM];
__device__ __align__(1024) bf16 g_act[SEQ * 1408];
__device__ __align__(1024) float2 g_stats[SEQ * 8];
__device__ __align__(1024) float g_cs[2 * 1408];

__device__ unsigned int g_team[64];
__device__ unsigned int g_ln_count[16];

__device__ __forceinline__ uint32_t smem_u32(const void* p) { return (uint32_t)__cvta_generic_to_shared(p); }
__device__ __forceinline__ void mbar_init(uint32_t bar, uint32_t cnt) {
  asm volatile("mbarrier.init.shared::cta.b64 [%0], %1;" ::"r"(bar), "r"(cnt));
}
__device__ __forceinline__ void mbar_expect_tx(uint32_t bar, uint32_t bytes) {
  asm volatile("mbarrier.arrive.expect_tx.shared::cta.b64 _, [%0], %1;" ::"r"(bar), "r"(bytes) : "memory");
}
__device__ __forceinline__ void mbar_arrive(uint32_t bar) {
  asm volatile("mbarrier.arrive.shared::cta.b64 _, [%0];" ::"r"(bar) : "memory");
}
__device__ __forceinline__ void mbar_wait(uint32_t bar, uint32_t parity) {
  asm volatile(
      "{\n.reg .pred p;\n.reg .u32 c;\n"
      "mov.u32 c, 0;\n"
      "WAIT_LOOP:\n"
      "mbarrier.try_wait.parity.shared::cta.b64 p, [%0], %1;\n"
      "@p bra WAIT_DONE;\n"
      "add.u32 c, c, 1;\n"
      "setp.lt.u32 p, c, 0x400000;\n"
      "@p bra WAIT_LOOP;\n"
      "trap;\n"
      "WAIT_DONE:\n}"
      ::"r"(bar), "r"(parity) : "memory");
}
__device__ __forceinline__ void spin_until(const unsigned int* ctr, unsigned int target) {
  asm volatile(
      "{\n.reg .pred p;\n.reg .u32 c, v;\n"
      "mov.u32 c, 0;\n"
      "SPIN_LOOP:\n"
      "ld.acquire.gpu.global.u32 v, [%0];\n"
      "setp.ge.u32 p, v, %1;\n"
      "@p bra SPIN_DONE;\n"
      "add.u32 c, c, 1;\n"
      "setp.lt.u32 p, c, 0x1000000;\n"
      "@p bra SPIN_LOOP;\n"
      "trap;\n"
      "SPIN_DONE:\n}"
      ::"l"(ctr), "r"(target) : "memory");
}
__device__ __forceinline__ void tma_load_2d(uint32_t dst, const CUtensorMap* map, int c0, int c1, uint32_t bar) {
  asm volatile("cp.async.bulk.tensor.2d.shared::cluster.global.mbarrier::complete_tx::bytes [%0], [%1, {%3, %4}], [%2];"
               ::"r"(dst), "l"(map), "r"(bar), "r"(c0), "r"(c1) : "memory");
}
__device__ __forceinline__ void tma_load_3d(uint32_t dst, const CUtensorMap* map, int c0, int c1, int c2, uint32_t bar) {
  asm volatile("cp.async.bulk.tensor.3d.shared::cluster.global.mbarrier::complete_tx::bytes [%0], [%1, {%3, %4, %5}], [%2];"
               ::"r"(dst), "l"(map), "r"(bar), "r"(c0), "r"(c1), "r"(c2) : "memory");
}
__device__ __forceinline__ void tma_store_2d(const CUtensorMap* map, uint32_t src, int c0, int c1) {
  asm volatile("cp.async.bulk.tensor.2d.global.shared::cta.bulk_group [%0, {%2, %3}], [%1];"
               ::"l"(map), "r"(src), "r"(c0), "r"(c1) : "memory");
}
__device__ __forceinline__ void tma_prefetch_desc(const CUtensorMap* map) {
  asm volatile("prefetch.tensormap [%0];" ::"l"(map) : "memory");
}
__device__ __forceinline__ void bulk_commit() { asm volatile("cp.async.bulk.commit_group;" ::: "memory"); }
template <int N> __device__ __forceinline__ void bulk_wait_read() { asm volatile("cp.async.bulk.wait_group.read %0;" ::"n"(N) : "memory"); }
__device__ __forceinline__ void fence_async_smem() { asm volatile("fence.proxy.async.shared::cta;" ::: "memory"); }
__device__ __forceinline__ void bar_sync(int id, int n) { asm volatile("bar.sync %0, %1;" ::"r"(id), "r"(n) : "memory"); }
__device__ __forceinline__ void bar_arrive(int id, int n) { asm volatile("bar.arrive %0, %1;" ::"r"(id), "r"(n) : "memory"); }
__device__ __forceinline__ void pdl_wait() { asm volatile("griddepcontrol.wait;" ::: "memory"); }
__device__ __forceinline__ void pdl_launch() { asm volatile("griddepcontrol.launch_dependents;" ::: "memory"); }
template <int N> __device__ __forceinline__ void reg_inc() { asm volatile("setmaxnreg.inc.sync.aligned.u32 %0;" ::"n"(N)); }
template <int N> __device__ __forceinline__ void reg_dec() { asm volatile("setmaxnreg.dec.sync.aligned.u32 %0;" ::"n"(N)); }
__device__ __forceinline__ void wgmma_fence() { asm volatile("wgmma.fence.sync.aligned;" ::: "memory"); }
__device__ __forceinline__ void wgmma_commit() { asm volatile("wgmma.commit_group.sync.aligned;" ::: "memory"); }
template <int N> __device__ __forceinline__ void wgmma_wait() { asm volatile("wgmma.wait_group.sync.aligned %0;" ::"n"(N) : "memory"); }
template <int N> __device__ __forceinline__ void fence_regs(float (&r)[N]) {
#pragma unroll
  for (int i = 0; i < N; i++) asm volatile("" : "+f"(r[i])::"memory");
}
template <int N> __device__ __forceinline__ void fence_regs(uint32_t (&r)[N]) {
#pragma unroll
  for (int i = 0; i < N; i++) asm volatile("" : "+r"(r[i])::"memory");
}
__device__ __forceinline__ uint32_t make_desc(uint32_t addr, uint32_t lbo_bytes) { return ((addr & 0x3FFFF) >> 4) | ((lbo_bytes >> 4) << 16); }
__device__ __forceinline__ uint32_t desc_add(uint32_t d, uint32_t bytes) { return d + (bytes >> 4); }
__device__ __forceinline__ uint32_t pack_bf16(float lo, float hi) {
  uint32_t r;
  asm("cvt.rn.bf16x2.f32 %0, %1, %2;" : "=r"(r) : "f"(hi), "f"(lo));
  return r;
}
__device__ __forceinline__ float bf_lo(uint32_t v) { return __uint_as_float(v << 16); }
__device__ __forceinline__ float bf_hi(uint32_t v) { return __uint_as_float(v & 0xffff0000u); }
__device__ __forceinline__ float ex2(float x) {
  float y;
  asm("ex2.approx.ftz.f32 %0, %1;" : "=f"(y) : "f"(x));
  return y;
}
__device__ __forceinline__ void stmatrix_x4(uint32_t addr, uint32_t a, uint32_t b, uint32_t c, uint32_t d) {
  asm volatile("stmatrix.sync.aligned.m8n8.x4.shared.b16 [%0], {%1, %2, %3, %4};"
               ::"r"(addr), "r"(a), "r"(b), "r"(c), "r"(d) : "memory");
}
__device__ __forceinline__ uint32_t align1024(uint32_t a) { return (a + 1023u) & ~1023u; }

template <int TB>
__device__ __forceinline__ void wgmma_ss_n128(float (&d)[64], uint32_t da, uint32_t db, int scale_d) {
  asm volatile("{\n.reg .pred p;\n.reg .b64 da, db;\nsetp.ne.b32 p, %66, 0;\nmov.b64 da, {%64, 0x40000040};\nmov.b64 db, {%65, 0x40000040};\n"
    "wgmma.mma_async.sync.aligned.m64n128k16.f32.bf16.bf16 "
    "{%0, %1, %2, %3, %4, %5, %6, %7, %8, %9, %10, %11, %12, %13, %14, %15, "
    "%16, %17, %18, %19, %20, %21, %22, %23, %24, %25, %26, %27, %28, %29, %30, %31, "
    "%32, %33, %34, %35, %36, %37, %38, %39, %40, %41, %42, %43, %44, %45, %46, %47, "
    "%48, %49, %50, %51, %52, %53, %54, %55, %56, %57, %58, %59, %60, %61, %62, %63}, "
    "da, db, p, 1, 1, 0, %67;\n}\n"
    :
      "+f"(d[0]), "+f"(d[1]), "+f"(d[2]), "+f"(d[3]), "+f"(d[4]), "+f"(d[5]), "+f"(d[6]), "+f"(d[7]),
      "+f"(d[8]), "+f"(d[9]), "+f"(d[10]), "+f"(d[11]), "+f"(d[12]), "+f"(d[13]), "+f"(d[14]), "+f"(d[15]),
      "+f"(d[16]), "+f"(d[17]), "+f"(d[18]), "+f"(d[19]), "+f"(d[20]), "+f"(d[21]), "+f"(d[22]), "+f"(d[23]),
      "+f"(d[24]), "+f"(d[25]), "+f"(d[26]), "+f"(d[27]), "+f"(d[28]), "+f"(d[29]), "+f"(d[30]), "+f"(d[31]),
      "+f"(d[32]), "+f"(d[33]), "+f"(d[34]), "+f"(d[35]), "+f"(d[36]), "+f"(d[37]), "+f"(d[38]), "+f"(d[39]),
      "+f"(d[40]), "+f"(d[41]), "+f"(d[42]), "+f"(d[43]), "+f"(d[44]), "+f"(d[45]), "+f"(d[46]), "+f"(d[47]),
      "+f"(d[48]), "+f"(d[49]), "+f"(d[50]), "+f"(d[51]), "+f"(d[52]), "+f"(d[53]), "+f"(d[54]), "+f"(d[55]),
      "+f"(d[56]), "+f"(d[57]), "+f"(d[58]), "+f"(d[59]), "+f"(d[60]), "+f"(d[61]), "+f"(d[62]), "+f"(d[63])
    : "r"(da), "r"(db), "r"(scale_d), "n"(TB));
}
template <int TB>
__device__ __forceinline__ void wgmma_rs_n128(float (&d)[64], uint32_t a0, uint32_t a1, uint32_t a2, uint32_t a3, uint32_t db, int scale_d) {
  asm volatile("{\n.reg .pred p;\n.reg .b64 db;\nsetp.ne.b32 p, %69, 0;\nmov.b64 db, {%68, 0x40000040};\n"
    "wgmma.mma_async.sync.aligned.m64n128k16.f32.bf16.bf16 "
    "{%0, %1, %2, %3, %4, %5, %6, %7, %8, %9, %10, %11, %12, %13, %14, %15, "
    "%16, %17, %18, %19, %20, %21, %22, %23, %24, %25, %26, %27, %28, %29, %30, %31, "
    "%32, %33, %34, %35, %36, %37, %38, %39, %40, %41, %42, %43, %44, %45, %46, %47, "
    "%48, %49, %50, %51, %52, %53, %54, %55, %56, %57, %58, %59, %60, %61, %62, %63}, "
    "{%64, %65, %66, %67}, db, p, 1, 1, %70;\n}\n"
    :
      "+f"(d[0]), "+f"(d[1]), "+f"(d[2]), "+f"(d[3]), "+f"(d[4]), "+f"(d[5]), "+f"(d[6]), "+f"(d[7]),
      "+f"(d[8]), "+f"(d[9]), "+f"(d[10]), "+f"(d[11]), "+f"(d[12]), "+f"(d[13]), "+f"(d[14]), "+f"(d[15]),
      "+f"(d[16]), "+f"(d[17]), "+f"(d[18]), "+f"(d[19]), "+f"(d[20]), "+f"(d[21]), "+f"(d[22]), "+f"(d[23]),
      "+f"(d[24]), "+f"(d[25]), "+f"(d[26]), "+f"(d[27]), "+f"(d[28]), "+f"(d[29]), "+f"(d[30]), "+f"(d[31]),
      "+f"(d[32]), "+f"(d[33]), "+f"(d[34]), "+f"(d[35]), "+f"(d[36]), "+f"(d[37]), "+f"(d[38]), "+f"(d[39]),
      "+f"(d[40]), "+f"(d[41]), "+f"(d[42]), "+f"(d[43]), "+f"(d[44]), "+f"(d[45]), "+f"(d[46]), "+f"(d[47]),
      "+f"(d[48]), "+f"(d[49]), "+f"(d[50]), "+f"(d[51]), "+f"(d[52]), "+f"(d[53]), "+f"(d[54]), "+f"(d[55]),
      "+f"(d[56]), "+f"(d[57]), "+f"(d[58]), "+f"(d[59]), "+f"(d[60]), "+f"(d[61]), "+f"(d[62]), "+f"(d[63])
    : "r"(a0), "r"(a1), "r"(a2), "r"(a3), "r"(db), "r"(scale_d), "n"(TB));
}
template <int TB>
__device__ __forceinline__ void wgmma_ss_n176(float (&d)[88], uint32_t da, uint32_t db, int scale_d) {
  asm volatile("{\n.reg .pred p;\n.reg .b64 da, db;\nsetp.ne.b32 p, %90, 0;\nmov.b64 da, {%88, 0x40000040};\nmov.b64 db, {%89, 0x40000040};\n"
    "wgmma.mma_async.sync.aligned.m64n176k16.f32.bf16.bf16 "
    "{%0, %1, %2, %3, %4, %5, %6, %7, %8, %9, %10, %11, %12, %13, %14, %15, "
    "%16, %17, %18, %19, %20, %21, %22, %23, %24, %25, %26, %27, %28, %29, %30, %31, "
    "%32, %33, %34, %35, %36, %37, %38, %39, %40, %41, %42, %43, %44, %45, %46, %47, "
    "%48, %49, %50, %51, %52, %53, %54, %55, %56, %57, %58, %59, %60, %61, %62, %63, "
    "%64, %65, %66, %67, %68, %69, %70, %71, %72, %73, %74, %75, %76, %77, %78, %79, "
    "%80, %81, %82, %83, %84, %85, %86, %87}, "
    "da, db, p, 1, 1, 0, %91;\n}\n"
    :
      "+f"(d[0]), "+f"(d[1]), "+f"(d[2]), "+f"(d[3]), "+f"(d[4]), "+f"(d[5]), "+f"(d[6]), "+f"(d[7]),
      "+f"(d[8]), "+f"(d[9]), "+f"(d[10]), "+f"(d[11]), "+f"(d[12]), "+f"(d[13]), "+f"(d[14]), "+f"(d[15]),
      "+f"(d[16]), "+f"(d[17]), "+f"(d[18]), "+f"(d[19]), "+f"(d[20]), "+f"(d[21]), "+f"(d[22]), "+f"(d[23]),
      "+f"(d[24]), "+f"(d[25]), "+f"(d[26]), "+f"(d[27]), "+f"(d[28]), "+f"(d[29]), "+f"(d[30]), "+f"(d[31]),
      "+f"(d[32]), "+f"(d[33]), "+f"(d[34]), "+f"(d[35]), "+f"(d[36]), "+f"(d[37]), "+f"(d[38]), "+f"(d[39]),
      "+f"(d[40]), "+f"(d[41]), "+f"(d[42]), "+f"(d[43]), "+f"(d[44]), "+f"(d[45]), "+f"(d[46]), "+f"(d[47]),
      "+f"(d[48]), "+f"(d[49]), "+f"(d[50]), "+f"(d[51]), "+f"(d[52]), "+f"(d[53]), "+f"(d[54]), "+f"(d[55]),
      "+f"(d[56]), "+f"(d[57]), "+f"(d[58]), "+f"(d[59]), "+f"(d[60]), "+f"(d[61]), "+f"(d[62]), "+f"(d[63]),
      "+f"(d[64]), "+f"(d[65]), "+f"(d[66]), "+f"(d[67]), "+f"(d[68]), "+f"(d[69]), "+f"(d[70]), "+f"(d[71]),
      "+f"(d[72]), "+f"(d[73]), "+f"(d[74]), "+f"(d[75]), "+f"(d[76]), "+f"(d[77]), "+f"(d[78]), "+f"(d[79]),
      "+f"(d[80]), "+f"(d[81]), "+f"(d[82]), "+f"(d[83]), "+f"(d[84]), "+f"(d[85]), "+f"(d[86]), "+f"(d[87])
    : "r"(da), "r"(db), "r"(scale_d), "n"(TB));
}
template <int TB>
__device__ __forceinline__ void wgmma_ss_n256(float (&d)[128], uint32_t da, uint32_t db, int scale_d) {
  asm volatile("{\n.reg .pred p;\n.reg .b64 da, db;\nsetp.ne.b32 p, %130, 0;\nmov.b64 da, {%128, 0x40000040};\nmov.b64 db, {%129, 0x40000040};\n"
    "wgmma.mma_async.sync.aligned.m64n256k16.f32.bf16.bf16 "
    "{%0, %1, %2, %3, %4, %5, %6, %7, %8, %9, %10, %11, %12, %13, %14, %15, "
    "%16, %17, %18, %19, %20, %21, %22, %23, %24, %25, %26, %27, %28, %29, %30, %31, "
    "%32, %33, %34, %35, %36, %37, %38, %39, %40, %41, %42, %43, %44, %45, %46, %47, "
    "%48, %49, %50, %51, %52, %53, %54, %55, %56, %57, %58, %59, %60, %61, %62, %63, "
    "%64, %65, %66, %67, %68, %69, %70, %71, %72, %73, %74, %75, %76, %77, %78, %79, "
    "%80, %81, %82, %83, %84, %85, %86, %87, %88, %89, %90, %91, %92, %93, %94, %95, "
    "%96, %97, %98, %99, %100, %101, %102, %103, %104, %105, %106, %107, %108, %109, %110, %111, "
    "%112, %113, %114, %115, %116, %117, %118, %119, %120, %121, %122, %123, %124, %125, %126, %127}, "
    "da, db, p, 1, 1, 0, %131;\n}\n"
    :
      "+f"(d[0]), "+f"(d[1]), "+f"(d[2]), "+f"(d[3]), "+f"(d[4]), "+f"(d[5]), "+f"(d[6]), "+f"(d[7]),
      "+f"(d[8]), "+f"(d[9]), "+f"(d[10]), "+f"(d[11]), "+f"(d[12]), "+f"(d[13]), "+f"(d[14]), "+f"(d[15]),
      "+f"(d[16]), "+f"(d[17]), "+f"(d[18]), "+f"(d[19]), "+f"(d[20]), "+f"(d[21]), "+f"(d[22]), "+f"(d[23]),
      "+f"(d[24]), "+f"(d[25]), "+f"(d[26]), "+f"(d[27]), "+f"(d[28]), "+f"(d[29]), "+f"(d[30]), "+f"(d[31]),
      "+f"(d[32]), "+f"(d[33]), "+f"(d[34]), "+f"(d[35]), "+f"(d[36]), "+f"(d[37]), "+f"(d[38]), "+f"(d[39]),
      "+f"(d[40]), "+f"(d[41]), "+f"(d[42]), "+f"(d[43]), "+f"(d[44]), "+f"(d[45]), "+f"(d[46]), "+f"(d[47]),
      "+f"(d[48]), "+f"(d[49]), "+f"(d[50]), "+f"(d[51]), "+f"(d[52]), "+f"(d[53]), "+f"(d[54]), "+f"(d[55]),
      "+f"(d[56]), "+f"(d[57]), "+f"(d[58]), "+f"(d[59]), "+f"(d[60]), "+f"(d[61]), "+f"(d[62]), "+f"(d[63]),
      "+f"(d[64]), "+f"(d[65]), "+f"(d[66]), "+f"(d[67]), "+f"(d[68]), "+f"(d[69]), "+f"(d[70]), "+f"(d[71]),
      "+f"(d[72]), "+f"(d[73]), "+f"(d[74]), "+f"(d[75]), "+f"(d[76]), "+f"(d[77]), "+f"(d[78]), "+f"(d[79]),
      "+f"(d[80]), "+f"(d[81]), "+f"(d[82]), "+f"(d[83]), "+f"(d[84]), "+f"(d[85]), "+f"(d[86]), "+f"(d[87]),
      "+f"(d[88]), "+f"(d[89]), "+f"(d[90]), "+f"(d[91]), "+f"(d[92]), "+f"(d[93]), "+f"(d[94]), "+f"(d[95]),
      "+f"(d[96]), "+f"(d[97]), "+f"(d[98]), "+f"(d[99]), "+f"(d[100]), "+f"(d[101]), "+f"(d[102]), "+f"(d[103]),
      "+f"(d[104]), "+f"(d[105]), "+f"(d[106]), "+f"(d[107]), "+f"(d[108]), "+f"(d[109]), "+f"(d[110]), "+f"(d[111]),
      "+f"(d[112]), "+f"(d[113]), "+f"(d[114]), "+f"(d[115]), "+f"(d[116]), "+f"(d[117]), "+f"(d[118]), "+f"(d[119]),
      "+f"(d[120]), "+f"(d[121]), "+f"(d[122]), "+f"(d[123]), "+f"(d[124]), "+f"(d[125]), "+f"(d[126]), "+f"(d[127])
    : "r"(da), "r"(db), "r"(scale_d), "n"(TB));
}
constexpr int KV_STAGES = 4;
constexpr int KV_STAGE_BYTES = 16384 + 32768;
constexpr int KV_SMEM = KV_STAGES * KV_STAGE_BYTES + 1024 + 256;

__device__ __forceinline__ void st_global_v4(void* p, uint32_t a, uint32_t b, uint32_t c, uint32_t d) {
  asm volatile("st.global.v4.b32 [%0], {%1, %2, %3, %4};" ::"l"(p), "r"(a), "r"(b), "r"(c), "r"(d) : "memory");
}

__device__ __forceinline__ int tile_matrix(int t, int c) { return (t == 2 || t == 5) ? 2 : (c >> 2); }
__device__ __forceinline__ int tile_pair(int t, int c) {
  if (t == 2) return 8 + c;
  if (t == 5) return c;
  const int group = t == 0 ? 3 : t == 1 ? 2 : t == 3 ? 1 : 0;
  return group * 4 + (c & 3);
}

__global__ void __launch_bounds__(384, 1)
qkv_kernel(const __grid_constant__ CUtensorMap mCkv, const __grid_constant__ CUtensorMap mXn, const __grid_constant__ CUtensorMap mWk,
           const __grid_constant__ CUtensorMap mWv, const __grid_constant__ CUtensorMap mWq, const bf16* __restrict__ x,
           const bf16* __restrict__ w_gate, const bf16* __restrict__ w_up) {
  extern __shared__ uint8_t smem_raw[];
  const uint32_t base = align1024(smem_u32(smem_raw));
  const uint32_t bars = base + KV_STAGES * KV_STAGE_BYTES;
  if (threadIdx.x == 0) {
    for (int i = 0; i < KV_STAGES; i++) {
      mbar_init(bars + i * 8, 1);
      mbar_init(bars + 64 + i * 8, 8);
    }
    asm volatile("fence.mbarrier_init.release.cluster;" ::: "memory");
  }
  if (threadIdx.x == 32) {
    tma_prefetch_desc(&mCkv);
    tma_prefetch_desc(&mWk);
    tma_prefetch_desc(&mWv);
    tma_prefetch_desc(&mXn);
    tma_prefetch_desc(&mWq);
  }
  if (blockIdx.x == 0 && threadIdx.x < 64) g_team[threadIdx.x] = 0;
  __syncthreads();
  pdl_launch();
  const int mblk = (((blockIdx.x >> 4) & 3) << 2) | (blockIdx.x & 3), ngrp = ((blockIdx.x >> 6) << 2) | ((blockIdx.x >> 2) & 3);
  const int wg = threadIdx.x >> 7, warp = (threadIdx.x >> 5) & 3, lane = threadIdx.x & 31;
  if (wg == 0) {
    reg_dec<56>();
    if (warp == 0) {
      if (lane == 0) {
        for (int it = 0; it < 48; it++) {
          const int t = it >> 3, k = it & 7, st = it & 3;
          const int mat = tile_matrix(t, ngrp), pair = tile_pair(t, ngrp);
          if (it == 16) {
            spin_until(g_ln_count + mblk, 24);
            asm volatile("fence.proxy.async.global;" ::: "memory");
          }
          mbar_wait(bars + 64 + st * 8, ((it >> 2) & 1) ^ 1);
          const uint32_t sa = base + st * KV_STAGE_BYTES;
          mbar_expect_tx(bars + st * 8, KV_STAGE_BYTES);
          if (mat == 2) tma_load_2d(sa, &mXn, 0, k * SEQ + mblk * 128, bars + st * 8);
          else tma_load_2d(sa, &mCkv, k * 64, mblk * 128, bars + st * 8);
          tma_load_3d(sa + 16384, mat == 0 ? &mWk : mat == 1 ? &mWv : &mWq, 0, k * 64, pair * 4, bars + st * 8);
        }
      }
    } else {
      {
        auto ld = [&](int r, uint4& v0, uint4& v1) {
          const uint4* src = reinterpret_cast<const uint4*>(x + (size_t)(blockIdx.x * 16 + r) * DM);
          v0 = __ldg(src + lane);
          v1 = __ldg(src + 32 + lane);
        };
        uint4 a0, a1, b0, b1;
        int r = warp - 1;
        ld(r, a0, a1);
        ld(r + 3, b0, b1);
        for (; r < 16; r += 3) {
          const uint32_t u[8] = {a0.x, a0.y, a0.z, a0.w, a1.x, a1.y, a1.z, a1.w};
          a0 = b0;
          a1 = b1;
          if (r + 6 < 16) ld(r + 6, b0, b1);
          float f[16];
          float s = 0.f;
#pragma unroll
          for (int i = 0; i < 8; i++) { f[2 * i] = bf_lo(u[i]); f[2 * i + 1] = bf_hi(u[i]); s += f[2 * i] + f[2 * i + 1]; }
#pragma unroll
          for (int o = 16; o > 0; o >>= 1) s += __shfl_xor_sync(0xffffffffu, s, o);
          const float mean = s * (1.f / DM);
          float q = 0.f;
#pragma unroll
          for (int i = 0; i < 16; i++) { f[i] -= mean; q += f[i] * f[i]; }
#pragma unroll
          for (int o = 16; o > 0; o >>= 1) q += __shfl_xor_sync(0xffffffffu, q, o);
          const float rstd = (0.08838834764831845f * 1.4426950408889634f) / sqrtf(q * (1.f / DM) + 1e-5f);
          uint4* dst = reinterpret_cast<uint4*>(g_xn + ((size_t)(lane >> 3) * SEQ + blockIdx.x * 16 + r) * 64) + (lane & 7);
          dst[0] = make_uint4(pack_bf16(f[0] * rstd, f[1] * rstd), pack_bf16(f[2] * rstd, f[3] * rstd),
                                 pack_bf16(f[4] * rstd, f[5] * rstd), pack_bf16(f[6] * rstd, f[7] * rstd));
          dst[4 * SEQ * 8] = make_uint4(pack_bf16(f[8] * rstd, f[9] * rstd), pack_bf16(f[10] * rstd, f[11] * rstd),
                                      pack_bf16(f[12] * rstd, f[13] * rstd), pack_bf16(f[14] * rstd, f[15] * rstd));
        }
      }
      __threadfence();
      __syncwarp();
      if (lane == 0) atomicAdd(g_ln_count + (blockIdx.x >> 3), 1u);
      const int task = blockIdx.x * 3 + (warp - 1);
      if (task < 352) {
        const int mat = task / 176, grp = task % 176;
        float a[8];
#pragma unroll
        for (int i = 0; i < 8; i++) a[i] = 0.f;
        if (grp < FF / 8) {
          const bf16* w = (mat ? w_up : w_gate) + grp * 8;
#pragma unroll 4
          for (int r = lane; r < DM; r += 32) {
            const uint4 v = __ldg(reinterpret_cast<const uint4*>(w + (size_t)r * FF));
            a[0] += bf_lo(v.x); a[1] += bf_hi(v.x); a[2] += bf_lo(v.y); a[3] += bf_hi(v.y);
            a[4] += bf_lo(v.z); a[5] += bf_hi(v.z); a[6] += bf_lo(v.w); a[7] += bf_hi(v.w);
          }
#pragma unroll
          for (int i = 0; i < 8; i++)
#pragma unroll
            for (int o = 16; o > 0; o >>= 1) a[i] += __shfl_xor_sync(0xffffffffu, a[i], o);
        }
        if (lane == 0) {
          float4* dst = reinterpret_cast<float4*>(g_cs + mat * 1408 + grp * 8);
          dst[0] = make_float4(a[0], a[1], a[2], a[3]);
          dst[1] = make_float4(a[4], a[5], a[6], a[7]);
        }
      }
    }
  } else {
    reg_inc<224>();
    const int cw = wg - 1;
    const int tid = threadIdx.x & 127;
    if (cw == 1) bar_arrive(1, 256);
    float acc[128];
    uint32_t pk[64];
    const size_t thr_off = (size_t)(mblk * 128 + cw * 64 + warp * 16 + (lane >> 2)) * 64 + (lane & 3) * 8;
    bf16* prev_out = nullptr;
    auto store_piece = [&](int i) {
      bf16* dst = prev_out + (size_t)(i >> 1) * SEQ * 64 + (i & 1) * 32;
      st_global_v4(dst, pk[8 * i], pk[8 * i + 2], pk[8 * i + 4], pk[8 * i + 6]);
      st_global_v4(dst + 8 * 64, pk[8 * i + 1], pk[8 * i + 3], pk[8 * i + 5], pk[8 * i + 7]);
    };
    for (int t = 0; t < 6; t++) {
#pragma unroll
      for (int k = 0; k < 8; k++) {
        const int st = k & 3;
        mbar_wait(bars + st * 8, (k >> 2) & 1);
        const uint32_t sa = base + st * KV_STAGE_BYTES;
        const uint32_t da = make_desc(sa + cw * 8192, 16);
        const uint32_t db = make_desc(sa + 16384, 8192);
        bar_sync(1 + cw, 256);
        wgmma_fence();
#pragma unroll
        for (int kk = 0; kk < 4; kk++) wgmma_ss_n256<1>(acc, desc_add(da, kk * 32), desc_add(db, kk * 2048), (k | kk) != 0);
        wgmma_commit();
        bar_arrive(2 - cw, 256);
        if (t > 0) store_piece(k);
        if (k > 0) {
          wgmma_wait<1>();
          if (lane == 0) mbar_arrive(bars + 64 + ((k - 1) & 3) * 8);
        }
      }
      wgmma_wait<0>();
      if (lane == 0) mbar_arrive(bars + 64 + 3 * 8);
      fence_regs(acc);
      const int mat = tile_matrix(t, ngrp);
#pragma unroll
      for (int i = 0; i < 64; i++) pk[i] = pack_bf16(acc[2 * i], acc[2 * i + 1]);
      prev_out = (mat == 0 ? g_k : mat == 1 ? g_v : g_q) + thr_off + (size_t)(tile_pair(t, ngrp) * 2) * SEQ * HD;
    }
#pragma unroll
    for (int i = 0; i < 8; i++) store_piece(i);
  }
}
constexpr int AT_SLOTS = 7;
constexpr int AT_SMEM = AT_SLOTS * 32768 + 1024 + 256;
struct AttnSched {
  int start[134];
  int tile[NH * 16];
};

struct RingPos {
  int slot;
  uint32_t phase;
  __device__ __forceinline__ void next() {
    if (++slot == AT_SLOTS) { slot = 0; phase ^= 1; }
  }
};

constexpr float SM_ZERO = 32.f;
constexpr float SM_LIMIT = 1099511627776.f;

template <int NG, bool SUB>
__device__ __forceinline__ void exp_pack(const float (&s)[64], uint32_t (&p)[32], float m0, float m1, float& r0, float& r1) {
  float a0 = 0.f, a1 = 0.f, b0 = 0.f, b1 = 0.f;
#pragma unroll
  for (int i = 0; i < NG; i++) {
    const float e0 = ex2(SUB ? s[4 * i] - m0 : s[4 * i]), e1 = ex2(SUB ? s[4 * i + 1] - m0 : s[4 * i + 1]);
    const float e2 = ex2(SUB ? s[4 * i + 2] - m1 : s[4 * i + 2]), e3 = ex2(SUB ? s[4 * i + 3] - m1 : s[4 * i + 3]);
    a0 += e0;
    b0 += e1;
    a1 += e2;
    b1 += e3;
    p[2 * i] = pack_bf16(e0, e1);
    p[2 * i + 1] = pack_bf16(e2, e3);
  }
#pragma unroll
  for (int i = 2 * NG; i < 32; i++) p[i] = 0u;
  r0 = a0 + b0;
  r1 = a1 + b1;
}

__device__ __forceinline__ void refresh_max(const float (&s)[64], float (&o)[64], float& m0, float& m1, float& l0, float& l1) {
  float a0 = fmaxf(s[0], s[1]), a1 = fmaxf(s[2], s[3]), b0 = fmaxf(s[4], s[5]), b1 = fmaxf(s[6], s[7]);
#pragma unroll
  for (int i = 2; i < 16; i += 2) {
    a0 = fmaxf(a0, fmaxf(s[4 * i], s[4 * i + 1]));
    a1 = fmaxf(a1, fmaxf(s[4 * i + 2], s[4 * i + 3]));
    b0 = fmaxf(b0, fmaxf(s[4 * i + 4], s[4 * i + 5]));
    b1 = fmaxf(b1, fmaxf(s[4 * i + 6], s[4 * i + 7]));
  }
  a0 = fmaxf(a0, b0);
  a1 = fmaxf(a1, b1);
  a0 = fmaxf(a0, __shfl_xor_sync(0xffffffffu, a0, 1));
  a1 = fmaxf(a1, __shfl_xor_sync(0xffffffffu, a1, 1));
  a0 = fmaxf(a0, __shfl_xor_sync(0xffffffffu, a0, 2));
  a1 = fmaxf(a1, __shfl_xor_sync(0xffffffffu, a1, 2));
  a0 = fmaxf(a0, m0);
  a1 = fmaxf(a1, m1);
  const float sc0 = ex2(m0 - a0), sc1 = ex2(m1 - a1);
  m0 = a0;
  m1 = a1;
  l0 *= sc0;
  l1 *= sc1;
#pragma unroll
  for (int i = 0; i < 16; i++) {
    o[4 * i] *= sc0;
    o[4 * i + 1] *= sc0;
    o[4 * i + 2] *= sc1;
    o[4 * i + 3] *= sc1;
  }
}

__device__ __forceinline__ void mask_diag(float (&s)[64], int cw, int warp, int lane) {
  const int t0 = cw * 64 + warp * 16 + (lane >> 2) - (lane & 3) * 2;
#pragma unroll
  for (int i = 0; i < 16; i++) {
    if (8 * i > t0) s[4 * i] = -INFINITY;
    if (8 * i + 1 > t0) s[4 * i + 1] = -INFINITY;
    if (8 * (i - 1) > t0) s[4 * i + 2] = -INFINITY;
    if (8 * (i - 1) + 1 > t0) s[4 * i + 3] = -INFINITY;
  }
}

__device__ __forceinline__ void load_q_frags(uint32_t (&q)[32], uint32_t sq, int cw, int warp, int lane) {
  const int row = cw * 64 + warp * 16 + (lane & 7) + ((lane >> 3) & 1) * 8;
  const uint32_t rbase = sq + row * 128;
#pragma unroll
  for (int j = 0; j < 8; j++) {
    const int chunk = (2 * j + (lane >> 4)) & 7;
    asm volatile("ldmatrix.sync.aligned.m8n8.x4.shared.b16 {%0, %1, %2, %3}, [%4];"
                 : "=r"(q[4 * j]), "=r"(q[4 * j + 1]), "=r"(q[4 * j + 2]), "=r"(q[4 * j + 3])
                 : "r"(rbase + (j >> 2) * 16384 + ((chunk ^ (row & 7)) << 4)) : "memory");
  }
}

__device__ __forceinline__ void row_recip(float l0, float l1, float& i0, float& i1) {
  l0 += __shfl_xor_sync(0xffffffffu, l0, 1);
  l1 += __shfl_xor_sync(0xffffffffu, l1, 1);
  l0 += __shfl_xor_sync(0xffffffffu, l0, 2);
  l1 += __shfl_xor_sync(0xffffffffu, l1, 2);
  asm("rcp.approx.ftz.f32 %0, %1;" : "=f"(i0) : "f"(l0));
  asm("rcp.approx.ftz.f32 %0, %1;" : "=f"(i1) : "f"(l1));
}
__device__ __forceinline__ void write_ctx(const float (&o)[64], float i0, float i1, bf16* dst) {
#pragma unroll
  for (int a = 0; a < 4; a++) {
    st_global_v4(dst + (a >> 1) * SEQ * 64 + (a & 1) * 32, pack_bf16(o[16 * a] * i0, o[16 * a + 1] * i0), pack_bf16(o[16 * a + 4] * i0, o[16 * a + 5] * i0),
                 pack_bf16(o[16 * a + 8] * i0, o[16 * a + 9] * i0), pack_bf16(o[16 * a + 12] * i0, o[16 * a + 13] * i0));
    st_global_v4(dst + (a >> 1) * SEQ * 64 + (a & 1) * 32 + 8 * 64, pack_bf16(o[16 * a + 2] * i1, o[16 * a + 3] * i1), pack_bf16(o[16 * a + 6] * i1, o[16 * a + 7] * i1),
                 pack_bf16(o[16 * a + 10] * i1, o[16 * a + 11] * i1), pack_bf16(o[16 * a + 14] * i1, o[16 * a + 15] * i1));
  }
}

__global__ void __launch_bounds__(384, 1)
attn_kernel(const __grid_constant__ CUtensorMap mQ, const __grid_constant__ CUtensorMap mK, const __grid_constant__ CUtensorMap mV,
            const __grid_constant__ AttnSched sched) {
  extern __shared__ uint8_t smem_raw[];
  const uint32_t base = align1024(smem_u32(smem_raw));
  const uint32_t bar_full = base + AT_SLOTS * 32768, bar_empty = bar_full + 64;
  if (threadIdx.x == 0) {
    for (int i = 0; i < AT_SLOTS; i++) {
      mbar_init(bar_full + i * 8, 1);
      mbar_init(bar_empty + i * 8, 8);
    }
    asm volatile("fence.mbarrier_init.release.cluster;" ::: "memory");
  }
  if (threadIdx.x == 32) {
    tma_prefetch_desc(&mQ);
    tma_prefetch_desc(&mK);
    tma_prefetch_desc(&mV);
  }
  __syncthreads();
  pdl_launch();
  const int wg = threadIdx.x >> 7, warp = (threadIdx.x >> 5) & 3, lane = threadIdx.x & 31;
  const int t_begin = sched.start[blockIdx.x], t_end = sched.start[blockIdx.x + 1];
  if (wg == 0) {
    reg_dec<24>();
    if (warp == 0 && lane == 0) {
      RingPos rp{0, 1};
      auto load = [&](const CUtensorMap* m, int row) {
        mbar_wait(bar_empty + rp.slot * 8, rp.phase);
        const uint32_t dst = base + rp.slot * 32768, fb = bar_full + rp.slot * 8;
        mbar_expect_tx(fb, 32768);
        tma_load_2d(dst, m, 0, row, fb);
        tma_load_2d(dst + 16384, m, 0, row + SEQ, fb);
        rp.next();
      };
      pdl_wait();
      int prev_v = -1;
      for (int ti = t_begin; ti < t_end; ti++) {
        const int tile = sched.tile[ti], h = tile >> 4, qb = tile & 15;
        if (ti == t_begin) load(&mQ, h * 2 * SEQ + qb * 128);
        for (int j = qb; j >= 0; j--) {
          if (prev_v >= 0) load(&mV, prev_v);
          prev_v = h * 2 * SEQ + (qb - j) * 128;
          load(&mK, prev_v);
          if (j == 0 && ti + 1 < t_end) {
            const int nt = sched.tile[ti + 1];
            load(&mQ, (nt >> 4) * 2 * SEQ + (nt & 15) * 128);
          }
        }
      }
      if (prev_v >= 0) load(&mV, prev_v);
    }
  } else {
    reg_inc<240>();
    const int cw = wg - 1;
    RingPos rp{0, 0};
    auto take = [&](int& slot) {
      mbar_wait(bar_full + rp.slot * 8, rp.phase);
      slot = rp.slot;
      rp.next();
    };
    auto release = [&](int slot) {
      if (lane == 0) mbar_arrive(bar_empty + slot * 8);
    };
    if (t_begin < t_end) {
      if (cw == 1) bar_arrive(1, 256);
      float s[64], o[64];
      uint32_t q[32], p[32];
      float m0, m1, l0 = 0.f, l1 = 0.f;
      auto ctx_ptr = [&](int t) {
        return g_ctx + (size_t)((t >> 4) * 2 * SEQ + (t & 15) * 128 + cw * 64 + warp * 16 + (lane >> 2)) * 64 + (lane & 3) * 8;
      };
      int slot_q = 0, slot_v = 0, slot_k = 0;
      auto issue_pv = [&](bool accumulate) {
        const uint32_t dv = make_desc(base + slot_v * 32768, 16384);
#pragma unroll
        for (int kk = 0; kk < 8; kk++)
          wgmma_rs_n128<1>(o, p[4 * kk], p[4 * kk + 1], p[4 * kk + 2], p[4 * kk + 3], desc_add(dv, kk * 2048), kk != 0 || accumulate);
      };
      auto issue_qk = [&]() {
        const uint32_t dk = make_desc(base + slot_k * 32768, 16);
#pragma unroll
        for (int kk = 0; kk < 8; kk++)
          wgmma_rs_n128<0>(s, q[4 * kk], q[4 * kk + 1], q[4 * kk + 2], q[4 * kk + 3],
                           desc_add(dk, (kk >> 2) * 16384 + (kk & 3) * 32), kk != 0);
      };
      auto take_next = [&](bool last_block, bool more_tiles) {
        if (last_block && more_tiles) take(slot_q);
        take(slot_v);
        if (!last_block || more_tiles) take(slot_k);
      };

      auto start_tile = [&]() {
        const float a0 = __shfl_sync(0xffffffffu, s[0], lane & 28), a1 = __shfl_sync(0xffffffffu, s[2], lane & 28);
        m0 = fabsf(a0) <= SM_ZERO ? 0.f : a0;
        m1 = fabsf(a1) <= SM_ZERO ? 0.f : a1;
        l0 = 0.f;
        l1 = 0.f;
      };

      int ti = t_begin;
      int j = sched.tile[ti] & 15;
      take(slot_q);
      load_q_frags(q, base + slot_q * 32768, cw, warp, lane);
      int done_q = slot_q;
      take(slot_k);
      bar_sync(1 + cw, 256);
      wgmma_fence();
      issue_qk();
      wgmma_commit();
      bar_arrive(2 - cw, 256);
      release(done_q);
      int done_k = slot_k;
      bool more = ti + 1 < t_end;
      take_next(j == 0, more);
#pragma unroll
      for (int i = 0; i < 64; i++) o[i] = 0.f;
      wgmma_wait<0>();
      release(done_k);
      fence_regs(s);
      start_tile();
      if (j == 0) mask_diag(s, cw, warp, lane);
      bool fresh = true;
#pragma unroll 1
      while (true) {
        float r0, r1;
        bool general = !__all_sync(0xffffffffu, m0 == 0.f && m1 == 0.f), refresh = false;
        if (!general) {
          exp_pack<16, false>(s, p, m0, m1, r0, r1);
          general = refresh = __any_sync(0xffffffffu, !(r0 <= SM_LIMIT && r1 <= SM_LIMIT));
        }
        if (general) {
#pragma unroll 1
          while (true) {
            if (refresh) refresh_max(s, o, m0, m1, l0, l1);
            exp_pack<16, true>(s, p, m0, m1, r0, r1);
            if (refresh || !__any_sync(0xffffffffu, !(r0 <= SM_LIMIT && r1 <= SM_LIMIT))) break;
            refresh = true;
          }
        }
        l0 += r0;
        l1 += r1;
        if (j == 0) {
          if (!more) break;
          load_q_frags(q, base + slot_q * 32768, cw, warp, lane);
          done_q = slot_q;
        }
        bar_sync(1 + cw, 256);
        wgmma_fence();
        issue_pv(!fresh);
        issue_qk();
        wgmma_commit();
        bar_arrive(2 - cw, 256);
        const int done_v = slot_v;
        done_k = slot_k;
        fresh = j == 0;
        if (fresh) release(done_q);
        if (fresh) {
          j = sched.tile[++ti] & 15;
          more = ti + 1 < t_end;
        } else {
          j--;
        }
        take_next(j == 0, more);
        float i0, i1;
        if (fresh) row_recip(l0, l1, i0, i1);
        wgmma_wait<0>();
        release(done_v);
        release(done_k);
        fence_regs(s);
        fence_regs(o);
        if (fresh) {
          write_ctx(o, i0, i1, ctx_ptr(sched.tile[ti - 1]));
          start_tile();
        }
        if (j == 0) mask_diag(s, cw, warp, lane);
      }
      bar_sync(1 + cw, 256);
      wgmma_fence();
      issue_pv(!fresh);
      wgmma_commit();
      bar_arrive(2 - cw, 256);
      float i0, i1;
      row_recip(l0, l1, i0, i1);
      wgmma_wait<0>();
      fence_regs(o);
      write_ctx(o, i0, i1, ctx_ptr(sched.tile[t_end - 1]));
    }
  }
}
constexpr int TL_XBUF = 196608;
constexpr int TL_CS = TL_XBUF + 32768;
constexpr int TL_BARS = TL_CS + 1408;
constexpr int TL_SMEM = TL_BARS + 192 + 1024;

__device__ __forceinline__ void tma_load_5d(uint32_t dst, const CUtensorMap* map, int c0, int c4, uint32_t bar) {
  asm volatile("cp.async.bulk.tensor.5d.shared::cluster.global.mbarrier::complete_tx::bytes [%0], [%1, {%3, %4, %4, %4, %5}], [%2];"
               ::"r"(dst), "l"(map), "r"(bar), "r"(c0), "r"(0), "r"(c4) : "memory");
}
__device__ __forceinline__ uint32_t relu_mul_bf16x2(uint32_t g, uint32_t u) {
  uint32_t r;
  asm("{\n.reg .b32 t;\nmax.NaN.bf16x2 t, %1, %3;\nmul.rn.bf16x2 %0, t, %2;\n}" : "=r"(r) : "r"(g), "r"(u), "r"(0u));
  return r;
}
__device__ __forceinline__ void team_arrive(unsigned int* ctr) {
  asm volatile("fence.acq_rel.gpu;\nred.relaxed.gpu.global.add.u32 [%0], 1;" ::"l"(ctr) : "memory");
}
__device__ __forceinline__ void st_global_v2(void* p, uint32_t a, uint32_t b) {
  asm volatile("st.global.v2.b32 [%0], {%1, %2};" ::"l"(p), "r"(a), "r"(b));
}

template <int NSTEPS>
__device__ __forceinline__ void gemm_split_k(float (&acc)[64], uint32_t base, uint32_t bar_full, int cw, int tid) {
  const uint32_t bar_empty = bar_full + 32;
#pragma unroll 1
  for (int s = 0; s < NSTEPS; s++) {
    const int st = s & 3;
    mbar_wait(bar_full + st * 8, (s >> 2) & 1);
    const uint32_t sa = base + st * 49152;
    const uint32_t da = make_desc(sa + cw * 8192, 16);
    const uint32_t db = make_desc(sa + 16384 + cw * 8192, 16384);
    wgmma_fence();
#pragma unroll
    for (int i = 0; i < 4; i++) wgmma_ss_n128<1>(acc, desc_add(da, i * 32), desc_add(db, i * 2048), (s | i) != 0);
    wgmma_commit();
    if (s > 0) {
      wgmma_wait<1>();
      if ((tid & 31) == 0) mbar_arrive(bar_empty + ((s - 1) & 3) * 8);
    }
  }
  wgmma_wait<0>();
  if ((tid & 31) == 0) mbar_arrive(bar_empty + ((NSTEPS - 1) & 3) * 8);
  fence_regs(acc);
}

template <int CW>
__device__ __forceinline__ void reduce_add_residual_t(const float (&acc)[64], const uint32_t (&res)[16], uint32_t (&pk)[16], uint32_t xbuf,
                                                      int tid) {
  constexpr int SEND = CW ? 0 : 32, KEEP = CW ? 32 : 0;
  const uint32_t wr = xbuf + CW * 16384 + tid * 16, rd = xbuf + (CW ^ 1) * 16384 + tid * 16;
#pragma unroll
  for (int i = 0; i < 8; i++)
    asm volatile("st.shared.v4.f32 [%0], {%1, %2, %3, %4};" ::"r"(wr + i * 2048), "f"(acc[SEND + 4 * i]), "f"(acc[SEND + 4 * i + 1]),
                 "f"(acc[SEND + 4 * i + 2]), "f"(acc[SEND + 4 * i + 3]) : "memory");
  bar_sync(1, 256);
#pragma unroll
  for (int i = 0; i < 8; i++) {
    float4 t;
    asm volatile("ld.shared.v4.f32 {%0, %1, %2, %3}, [%4];" : "=f"(t.x), "=f"(t.y), "=f"(t.z), "=f"(t.w) : "r"(rd + i * 2048) : "memory");
    const uint32_t p0 = pack_bf16(t.x + acc[KEEP + 4 * i], t.y + acc[KEEP + 4 * i + 1]);
    const uint32_t p1 = pack_bf16(t.z + acc[KEEP + 4 * i + 2], t.w + acc[KEEP + 4 * i + 3]);
    pk[2 * i] = pack_bf16(bf_lo(p0) + bf_lo(res[2 * i]), bf_hi(p0) + bf_hi(res[2 * i]));
    pk[2 * i + 1] = pack_bf16(bf_lo(p1) + bf_lo(res[2 * i + 1]), bf_hi(p1) + bf_hi(res[2 * i + 1]));
  }
}
__device__ __forceinline__ void reduce_add_residual(const float (&acc)[64], const uint32_t (&res)[16], uint32_t (&pk)[16], uint32_t xbuf,
                                                    int cw, int tid) {
  if (cw == 0) reduce_add_residual_t<0>(acc, res, pk, xbuf, tid);
  else reduce_add_residual_t<1>(acc, res, pk, xbuf, tid);
}

__global__ void __launch_bounds__(384, 1)
tail_kernel(const __grid_constant__ CUtensorMap mCtx, const __grid_constant__ CUtensorMap mWo, const __grid_constant__ CUtensorMap mH,
            const __grid_constant__ CUtensorMap mWg, const __grid_constant__ CUtensorMap mWu, const __grid_constant__ CUtensorMap mAct,
            const __grid_constant__ CUtensorMap mWd, const __grid_constant__ CUtensorMap mOut, const bf16* __restrict__ x) {
  extern __shared__ uint8_t smem_raw[];
  const uint32_t base = align1024(smem_u32(smem_raw));
  const uint32_t barC = base + TL_BARS, barD = barC + 64, barE = barD + 64;
  if (threadIdx.x == 0) {
    for (int i = 0; i < 12; i++) {
      mbar_init(barC + (i >> 2) * 64 + (i & 3) * 8, 1);
      mbar_init(barC + (i >> 2) * 64 + 32 + (i & 3) * 8, 8);
    }
    asm volatile("fence.mbarrier_init.release.cluster;" ::: "memory");
  }
  if (threadIdx.x == 32) {
    tma_prefetch_desc(&mWo);
    tma_prefetch_desc(&mCtx);
    tma_prefetch_desc(&mWg);
    tma_prefetch_desc(&mWu);
    tma_prefetch_desc(&mH);
    tma_prefetch_desc(&mWd);
    tma_prefetch_desc(&mAct);
    tma_prefetch_desc(&mOut);
  }
  __syncthreads();
  const int team = blockIdx.x >> 3, member = blockIdx.x & 7;
  const int mhalf = member >> 2, nt = member & 3;
  const int m64 = team * 2 + mhalf;
  const int n0 = member * 176;
  const int wg = threadIdx.x >> 7, warp = (threadIdx.x >> 5) & 3, lane = threadIdx.x & 31;
  if (wg == 0) {
    reg_dec<40>();
    if (warp == 0 && lane == 0) {
      auto load_wo = [&](int s) {
        const uint32_t dst = base + (s & 3) * 49152, fb = barC + (s & 3) * 8;
        mbar_expect_tx(fb, 49152);
        tma_load_2d(dst + 16384, &mWo, nt * 128, (NH - 1 - s) * 128, fb);
        tma_load_2d(dst + 32768, &mWo, nt * 128 + 64, (NH - 1 - s) * 128, fb);
      };
      for (int s = 0; s < 4; s++) load_wo(s);
      pdl_wait();
      for (int s = 0; s < NH; s++) {
        const uint32_t dst = base + (s & 3) * 49152, fb = barC + (s & 3) * 8;
        if (s >= 4) {
          mbar_wait(barC + 32 + (s & 3) * 8, ((s >> 2) & 1) ^ 1);
          load_wo(s);
        }
        tma_load_2d(dst, &mCtx, 0, (NH - 1 - s) * 2 * SEQ + m64 * 64, fb);
        tma_load_2d(dst + 8192, &mCtx, 0, (NH - 1 - s) * 2 * SEQ + SEQ + m64 * 64, fb);
      }
      for (int it = 0; it < 8; it++) {
        const int st = it % 3;
        if (it < 3) {
          if (it == 0) mbar_wait(barC + 32, 1);
          mbar_wait(barC + 32 + (it + 1) * 8, 1);
        } else {
          mbar_wait(barD + 32 + st * 8, ((it / 3) & 1) ^ 1);
        }
        const uint32_t dst = base + st * 65536, fb = barD + st * 8;
        mbar_expect_tx(fb, 65536);
#pragma unroll
        for (int c = 0; c < 3; c++) {
          tma_load_5d(dst + 16384 + c * 8192, &mWg, n0 + c * 64, it * 2, fb);
          tma_load_5d(dst + 40960 + c * 8192, &mWu, n0 + c * 64, it * 2, fb);
        }
        if (it == 2) {
          spin_until(g_team + team * 4, 16);
          asm volatile("fence.proxy.async.global;" ::: "memory");
          tma_load_2d(base, &mH, 0, team * 128, barD);
          tma_load_2d(base + 65536, &mH, 0, SEQ + team * 128, barD + 8);
        }
        if (it >= 2) tma_load_2d(dst, &mH, 0, it * SEQ + team * 128, fb);
      }
      for (int s = 0; s < 11; s++) {
        const int st = s & 3;
        if (s < 4) {
          if (s == 0) mbar_wait(barD + 32, 0);
          if (s == 1) mbar_wait(barD + 32 + 8, 0);
          if (s == 2) mbar_wait(barD + 32 + 16, 1);
        } else {
          mbar_wait(barE + 32 + st * 8, ((s >> 2) & 1) ^ 1);
        }
        const uint32_t dst = base + st * 49152, fb = barE + st * 8;
        mbar_expect_tx(fb, 49152);
        tma_load_5d(dst + 16384, &mWd, nt * 128, s * 8, fb);
        tma_load_5d(dst + 32768, &mWd, nt * 128 + 64, s * 8, fb);
        if (s == 3) {
          spin_until(g_team + team * 4 + 1, 16);
          asm volatile("fence.proxy.async.global;" ::: "memory");
          for (int i = 0; i < 3; i++) {
            tma_load_2d(base + i * 49152, &mAct, 0, 2 * i * SEQ + m64 * 64, barE + i * 8);
            tma_load_2d(base + i * 49152 + 8192, &mAct, 0, (2 * i + 1) * SEQ + m64 * 64, barE + i * 8);
          }
        }
        if (s >= 3) {
          tma_load_2d(dst, &mAct, 0, 2 * s * SEQ + m64 * 64, fb);
          tma_load_2d(dst + 8192, &mAct, 0, (2 * s + 1) * SEQ + m64 * 64, fb);
        }
      }
    } else if (warp == 1) {
      pdl_wait();
      if (blockIdx.x == 0 && lane < 16) g_ln_count[lane] = 0;
      for (int i = lane; i < 352; i += 32) {
        const float c = __ldcg(g_cs + (i / 176) * 1408 + n0 + (i % 176));
        asm volatile("st.shared.f32 [%0], %1;" ::"r"(base + TL_CS + i * 4), "f"(c) : "memory");
      }
      bar_arrive(4, 288);
    }
  } else {
    reg_inc<232>();
    const int cw = wg - 1;
    const int tid = threadIdx.x & 127;
    const uint32_t xbuf = base + TL_XBUF;
    uint32_t hk[16];
    const int row0 = m64 * 64 + warp * 16 + (lane >> 2);
    {
      const int col0 = nt * 128 + cw * 64 + (lane & 3) * 2;
      uint32_t res[16];
#pragma unroll
      for (int i = 0; i < 8; i++) {
        res[2 * i] = __ldg(reinterpret_cast<const uint32_t*>(x + (size_t)row0 * DM + col0 + 8 * i));
        res[2 * i + 1] = __ldg(reinterpret_cast<const uint32_t*>(x + (size_t)(row0 + 8) * DM + col0 + 8 * i));
      }
      float acc[64];
      gemm_split_k<NH>(acc, base, barC, cw, tid);
      reduce_add_residual(acc, res, hk, xbuf, cw, tid);
      bf16* const hp = g_h + ((size_t)(nt * 2 + cw) * SEQ + row0) * 64 + (lane & 3) * 8;
#pragma unroll
      for (int a = 0; a < 2; a++) {
        st_global_v4(hp + 32 * a, hk[8 * a], hk[8 * a + 2], hk[8 * a + 4], hk[8 * a + 6]);
        st_global_v4(hp + 32 * a + 8 * 64, hk[8 * a + 1], hk[8 * a + 3], hk[8 * a + 5], hk[8 * a + 7]);
      }
      bar_sync(2 + cw, 128);
      if (tid == 0) team_arrive(g_team + team * 4);
      float s0 = 0.f, s1 = 0.f;
#pragma unroll
      for (int i = 0; i < 8; i++) {
        s0 += bf_lo(hk[2 * i]) + bf_hi(hk[2 * i]);
        s1 += bf_lo(hk[2 * i + 1]) + bf_hi(hk[2 * i + 1]);
      }
      s0 += __shfl_xor_sync(0xffffffffu, s0, 1); s1 += __shfl_xor_sync(0xffffffffu, s1, 1);
      s0 += __shfl_xor_sync(0xffffffffu, s0, 2); s1 += __shfl_xor_sync(0xffffffffu, s1, 2);
      const float mu0 = s0 * (1.f / 64), mu1 = s1 * (1.f / 64);
      float q0 = 0.f, q1 = 0.f;
#pragma unroll
      for (int i = 0; i < 8; i++) {
        const float a = bf_lo(hk[2 * i]) - mu0, b = bf_hi(hk[2 * i]) - mu0, c = bf_lo(hk[2 * i + 1]) - mu1, d = bf_hi(hk[2 * i + 1]) - mu1;
        q0 += a * a + b * b;
        q1 += c * c + d * d;
      }
      q0 += __shfl_xor_sync(0xffffffffu, q0, 1); q1 += __shfl_xor_sync(0xffffffffu, q1, 1);
      q0 += __shfl_xor_sync(0xffffffffu, q0, 2); q1 += __shfl_xor_sync(0xffffffffu, q1, 2);
      if ((lane & 3) == 0) {
        g_stats[row0 * 8 + nt * 2 + cw] = make_float2(mu0, q0);
        g_stats[(row0 + 8) * 8 + nt * 2 + cw] = make_float2(mu1, q1);
      }
      bar_sync(2 + cw, 128);
      if (tid == 0) team_arrive(g_team + team * 4 + 2);
    }
    {
      float ag[88], au[88];
      float mean[2], rstd[2];
      int st = 0, prev = 0;
      uint32_t ph = 0;
#pragma unroll 1
      for (int it = 0; it < 8; it++) {
        mbar_wait(barD + st * 8, ph);
        const uint32_t sa = base + st * 65536;
        const uint32_t da = make_desc(sa + cw * 8192, 16);
        const uint32_t dg = make_desc(sa + 16384, 8192);
        const uint32_t du = make_desc(sa + 40960, 8192);
        wgmma_fence();
#pragma unroll
        for (int kk = 0; kk < 4; kk++) {
          wgmma_ss_n176<1>(ag, desc_add(da, kk * 32), desc_add(dg, kk * 2048), (it | kk) != 0);
          wgmma_ss_n176<1>(au, desc_add(da, kk * 32), desc_add(du, kk * 2048), (it | kk) != 0);
        }
        wgmma_commit();
        if (it > 0) {
          wgmma_wait<1>();
          if (lane == 0) mbar_arrive(barD + 32 + prev * 8);
        }
        prev = st;
        if (++st == 3) { st = 0; ph ^= 1; }
      }
      if (tid == 0) spin_until(g_team + team * 4 + 2, 16);
      bar_sync(2 + cw, 128);
      const int drow = team * 128 + cw * 64 + warp * 16 + (lane >> 2);
#pragma unroll
      for (int r = 0; r < 2; r++) {
        const float4* sp = reinterpret_cast<const float4*>(g_stats + (drow + 8 * r) * 8);
        const float4 a = __ldcg(sp), b = __ldcg(sp + 1), c = __ldcg(sp + 2), d = __ldcg(sp + 3);
        const float mu = (a.x + a.z + b.x + b.z + c.x + c.z + d.x + d.z) * 0.125f;
        float m2 = a.y + a.w + b.y + b.w + c.y + c.w + d.y + d.w;
        m2 += 64.f * ((a.x - mu) * (a.x - mu) + (a.z - mu) * (a.z - mu) + (b.x - mu) * (b.x - mu) + (b.z - mu) * (b.z - mu) +
                      (c.x - mu) * (c.x - mu) + (c.z - mu) * (c.z - mu) + (d.x - mu) * (d.x - mu) + (d.z - mu) * (d.z - mu));
        mean[r] = mu;
        rstd[r] = 1.f / sqrtf(m2 * (1.f / DM) + 1e-5f);
      }
      bar_sync(4, 288);
      wgmma_wait<0>();
      if (lane == 0) mbar_arrive(barD + 32 + prev * 8);
      fence_regs(ag);
      fence_regs(au);
      bf16* const actp = g_act + (size_t)drow * 64 + (lane & 3) * 4;
      uint32_t csb = base + TL_CS + (lane & 3) * 8;
      asm volatile("" : "+r"(csb)::"memory");
#pragma unroll
      for (int j = 0; j < 11; j++) {
        uint32_t o4[4];
#pragma unroll
        for (int hh = 0; hh < 2; hh++) {
          const int i = 2 * j + hh;
          float2 cg, cu;
          asm("ld.shared.v2.f32 {%0, %1}, [%2];" : "=f"(cg.x), "=f"(cg.y) : "r"(csb + i * 32));
          asm("ld.shared.v2.f32 {%0, %1}, [%2];" : "=f"(cu.x), "=f"(cu.y) : "r"(csb + 704 + i * 32));
#pragma unroll
          for (int r = 0; r < 2; r++) {
            const uint32_t g = pack_bf16(fmaf(-mean[r], cg.x, ag[4 * i + 2 * r]) * rstd[r], fmaf(-mean[r], cg.y, ag[4 * i + 2 * r + 1]) * rstd[r]);
            const uint32_t u = pack_bf16(fmaf(-mean[r], cu.x, au[4 * i + 2 * r]) * rstd[r], fmaf(-mean[r], cu.y, au[4 * i + 2 * r + 1]) * rstd[r]);
            o4[2 * hh + r] = relu_mul_bf16x2(g, u);
          }
        }
        const int c = n0 + j * 16;
        bf16* const ap = actp + (size_t)(c >> 6) * SEQ * 64 + (c & 63);
        st_global_v2(ap, o4[0], o4[2]);
        st_global_v2(ap + 8 * 64, o4[1], o4[3]);
      }
      bar_sync(2 + cw, 128);
      if (tid == 0) team_arrive(g_team + team * 4 + 1);
    }
    {
      float acc[64];
      gemm_split_k<11>(acc, base, barE, cw, tid);
      uint32_t pk[16];
      reduce_add_residual(acc, hk, pk, xbuf, cw, tid);
      const uint32_t mystag = xbuf + (cw ^ 1) * 16384;
      bar_sync(2 + cw, 128);
      const int row = warp * 16 + (lane & 7) + ((lane >> 3) & 1) * 8;
#pragma unroll
      for (int j = 0; j < 4; j++) {
        const int chunk = 2 * j + (lane >> 4);
        stmatrix_x4(mystag + row * 128 + ((chunk ^ (row & 7)) << 4), pk[4 * j], pk[4 * j + 1], pk[4 * j + 2], pk[4 * j + 3]);
      }
      fence_async_smem();
      bar_sync(2 + cw, 128);
      if (tid == 0) {
        tma_store_2d(&mOut, mystag, nt * 128 + cw * 64, m64 * 64);
        bulk_commit();
        bulk_wait_read<0>();
      }
    }
  }
}
typedef CUresult (*EncodeTiledFn)(CUtensorMap*, CUtensorMapDataType, cuuint32_t, void*, const cuuint64_t*, const cuuint64_t*,
                                  const cuuint32_t*, const cuuint32_t*, CUtensorMapInterleave, CUtensorMapSwizzle,
                                  CUtensorMapL2promotion, CUtensorMapFloatOOBfill);

EncodeTiledFn encode_fn() {
  static EncodeTiledFn fn = nullptr;
  if (!fn) {
    void* p = nullptr;
    cudaDriverEntryPointQueryResult q;
    cudaGetDriverEntryPoint("cuTensorMapEncodeTiled", &p, cudaEnableDefault, &q);
    fn = (EncodeTiledFn)p;
  }
  return fn;
}

CUtensorMap map2d(const void* ptr, uint64_t inner, uint64_t outer, uint64_t pitch_elems, uint32_t box_inner, uint32_t box_outer,
                  CUtensorMapSwizzle sw = CU_TENSOR_MAP_SWIZZLE_128B) {
  CUtensorMap m;
  cuuint64_t dims[2] = {inner, outer};
  cuuint64_t strides[1] = {pitch_elems * 2};
  cuuint32_t box[2] = {box_inner, box_outer};
  cuuint32_t es[2] = {1, 1};
  encode_fn()(&m, CU_TENSOR_MAP_DATA_TYPE_BFLOAT16, 2, const_cast<void*>(ptr), dims, strides, box, es, CU_TENSOR_MAP_INTERLEAVE_NONE, sw,
              CU_TENSOR_MAP_L2_PROMOTION_L2_128B, CU_TENSOR_MAP_FLOAT_OOB_FILL_NONE);
  return m;
}

CUtensorMap map3d_chunks(const void* ptr, uint64_t rows, uint64_t cols, uint32_t box_rows, uint32_t chunks) {
  CUtensorMap m;
  cuuint64_t dims[3] = {64, rows, cols / 64};
  cuuint64_t strides[2] = {cols * 2, 128};
  cuuint32_t box[3] = {64, box_rows, chunks};
  cuuint32_t es[3] = {1, 1, 1};
  encode_fn()(&m, CU_TENSOR_MAP_DATA_TYPE_BFLOAT16, 3, const_cast<void*>(ptr), dims, strides, box, es, CU_TENSOR_MAP_INTERLEAVE_NONE,
              CU_TENSOR_MAP_SWIZZLE_128B, CU_TENSOR_MAP_L2_PROMOTION_L2_128B, CU_TENSOR_MAP_FLOAT_OOB_FILL_NONE);
  return m;
}

CUtensorMap map5d_perm32(const void* ptr, uint64_t rows, uint64_t cols, uint32_t groups) {
  CUtensorMap m;
  const cuuint64_t row = cols * 2;
  cuuint64_t dims[5] = {cols, 2, 4, 4, rows / 32};
  cuuint64_t strides[4] = {row, 8 * row, 2 * row, 32 * row};
  cuuint32_t box[5] = {64, 2, 4, 4, groups};
  cuuint32_t es[5] = {1, 1, 1, 1, 1};
  encode_fn()(&m, CU_TENSOR_MAP_DATA_TYPE_BFLOAT16, 5, const_cast<void*>(ptr), dims, strides, box, es, CU_TENSOR_MAP_INTERLEAVE_NONE,
              CU_TENSOR_MAP_SWIZZLE_128B, CU_TENSOR_MAP_L2_PROMOTION_L2_128B, CU_TENSOR_MAP_FLOAT_OOB_FILL_NONE);
  return m;
}
CUtensorMap map5d_perm16(const void* ptr, uint64_t rows, uint64_t cols, uint32_t groups) {
  CUtensorMap m;
  const cuuint64_t row = cols * 2;
  cuuint64_t dims[5] = {cols, 2, 2, 4, rows / 16};
  cuuint64_t strides[4] = {row, 8 * row, 2 * row, 16 * row};
  cuuint32_t box[5] = {64, 2, 2, 4, groups};
  cuuint32_t es[5] = {1, 1, 1, 1, 1};
  encode_fn()(&m, CU_TENSOR_MAP_DATA_TYPE_BFLOAT16, 5, const_cast<void*>(ptr), dims, strides, box, es, CU_TENSOR_MAP_INTERLEAVE_NONE,
              CU_TENSOR_MAP_SWIZZLE_128B, CU_TENSOR_MAP_L2_PROMOTION_L2_128B, CU_TENSOR_MAP_FLOAT_OOB_FILL_NONE);
  return m;
}

template <typename T> void* sym_addr(T& sym) {
  void* p = nullptr;
  cudaGetSymbolAddress(&p, sym);
  return p;
}

void build_schedule(AttnSched& s, int ncta) {
  static int lists[134][64];
  int cnt[134] = {0};
  float load[134] = {0};
  auto cost = [](int tile) { return (float)((tile & 15) + 1) + 0.65f; };
  constexpr int GROUP = 8;
  for (int g = 0; g < NH / GROUP; g++)
    for (int qb = 15; qb >= 0; qb--)
      for (int h = g * GROUP; h < (g + 1) * GROUP; h++) {
        int best = 0;
        for (int c = 1; c < ncta; c++)
          if (load[c] < load[best]) best = c;
        lists[best][cnt[best]++] = h * 16 + qb;
        load[best] += cost(h * 16 + qb);
      }
  for (int iter = 0; iter < 4000; iter++) {
    int hi = 0;
    for (int c = 1; c < ncta; c++)
      if (load[c] > load[hi]) hi = c;
    float best_max = load[hi] - 1e-3f;
    int bi = -1, bc = -1, bj = -1;
    for (int c = 0; c < ncta; c++) {
      if (c == hi) continue;
      for (int i = 0; i < cnt[hi]; i++) {
        const float ci = cost(lists[hi][i]);
        for (int j = 0; j < cnt[c]; j++) {
          if (lists[c][j] / (16 * GROUP) != lists[hi][i] / (16 * GROUP)) continue;
          const float cj = cost(lists[c][j]);
          const float m = fmaxf(load[hi] - ci + cj, load[c] - cj + ci);
          if (m < best_max) { best_max = m; bi = i; bc = c; bj = j; }
        }
      }
    }
    if (bi < 0) break;
    const int ti = lists[hi][bi], tj = lists[bc][bj];
    lists[hi][bi] = tj;
    lists[bc][bj] = ti;
    load[hi] += cost(tj) - cost(ti);
    load[bc] += cost(ti) - cost(tj);
  }
  int pos = 0;
  for (int c = 0; c < ncta; c++) {
    s.start[c] = pos;
    for (int i = 0; i < cnt[c]; i++) s.tile[pos++] = lists[c][i];
  }
  for (int c = ncta; c < 134; c++) s.start[c] = pos;
}

template <typename... KArgs, typename... Args>
void launch(void (*kern)(KArgs...), int grid, int smem, bool pdl, Args... args) {
  cudaLaunchConfig_t cfg = {};
  cfg.gridDim = dim3(grid);
  cfg.blockDim = dim3(384);
  cfg.dynamicSmemBytes = smem;
  cfg.stream = cudaStreamPerThread;
  cudaLaunchAttribute at[1];
  at[0].id = cudaLaunchAttributeProgrammaticStreamSerialization;
  at[0].val.programmaticStreamSerializationAllowed = 1;
  cfg.attrs = at;
  cfg.numAttrs = pdl ? 1 : 0;
  cudaLaunchKernelEx(&cfg, kern, KArgs(args)...);
}

}

extern "C" void kernel_launch(void* const* d_in, const int* in_sizes, int n_in, void* d_out, int out_size) {
  const bf16* x = (const bf16*)d_in[0];
  const bf16* ckv = (const bf16*)d_in[1];
  const bf16* wq = (const bf16*)d_in[2];
  const bf16* wuk = (const bf16*)d_in[3];
  const bf16* wuv = (const bf16*)d_in[4];
  const bf16* wo = (const bf16*)d_in[5];
  const bf16* wgate = (const bf16*)d_in[7];
  const bf16* wup = (const bf16*)d_in[8];
  const bf16* wdown = (const bf16*)d_in[9];
  bf16* out = (bf16*)d_out;

  static bool init = false;
  static AttnSched sched;
  static int nsm = 132;
  static void *p_xn, *p_q, *p_k, *p_v, *p_ctx, *p_h, *p_act;
  if (!init) {
    cudaFuncSetAttribute(qkv_kernel, cudaFuncAttributeMaxDynamicSharedMemorySize, KV_SMEM);
    cudaFuncSetAttribute(attn_kernel, cudaFuncAttributeMaxDynamicSharedMemorySize, AT_SMEM);
    cudaFuncSetAttribute(tail_kernel, cudaFuncAttributeMaxDynamicSharedMemorySize, TL_SMEM);
    int dev = 0;
    cudaGetDevice(&dev);
    cudaDeviceGetAttribute(&nsm, cudaDevAttrMultiProcessorCount, dev);
    if (nsm > 132) nsm = 132;
    build_schedule(sched, nsm);
    p_xn = sym_addr(g_xn); p_q = sym_addr(g_q); p_k = sym_addr(g_k); p_v = sym_addr(g_v); p_ctx = sym_addr(g_ctx); p_h = sym_addr(g_h); p_act = sym_addr(g_act);
    init = true;
  }

  const CUtensorMap mCkv = map2d(ckv, DM, SEQ, DM, 64, 128);
  const CUtensorMap mXn = map2d(p_xn, 64, 8 * SEQ, 64, 64, 128);
  const CUtensorMap mWk = map3d_chunks(wuk, DM, NH * HD, 64, 4);
  const CUtensorMap mWv = map3d_chunks(wuv, DM, NH * HD, 64, 4);
  const CUtensorMap mWq = map3d_chunks(wq, DM, NH * HD, 64, 4);
  launch(qkv_kernel, 128, KV_SMEM, false, mCkv, mXn, mWk, mWv, mWq, x, wgate, wup);

  const CUtensorMap mQ = map2d(p_q, 64, NH * 2 * SEQ, 64, 64, 128);
  const CUtensorMap mK = map2d(p_k, 64, NH * 2 * SEQ, 64, 64, 128);
  const CUtensorMap mV = map2d(p_v, 64, NH * 2 * SEQ, 64, 64, 128);
  launch(attn_kernel, nsm, AT_SMEM, true, mQ, mK, mV, sched);

  const CUtensorMap mCtx = map2d(p_ctx, 64, NH * 2 * SEQ, 64, 64, 64);
  const CUtensorMap mWo = map2d(wo, DM, NH * HD, DM, 64, 128);
  const CUtensorMap mH = map2d(p_h, 64, 8 * SEQ, 64, 64, 128);
  const CUtensorMap mWg = map5d_perm32(wgate, DM, FF, 2);
  const CUtensorMap mWu = map5d_perm32(wup, DM, FF, 2);
  const CUtensorMap mAct = map2d(p_act, 64, 22 * SEQ, 64, 64, 64);
  const CUtensorMap mWd = map5d_perm16(wdown, FF, DM, 8);
  const CUtensorMap mOut = map2d(out, DM, SEQ, DM, 64, 64);
  launch(tail_kernel, 128, TL_SMEM, true, mCtx, mWo, mH, mWg, mWu, mAct, mWd, mOut, x);
}
```
